```python
import torch

def _softmax(x, axis=-1):
    return torch.softmax(x, dim=axis)
def _gelu(x):
    return torch.nn.functional.gelu(x, approximate="tanh")
def _silu(x):
    return torch.nn.functional.silu(x)
def _sigmoid(x):
    return torch.sigmoid(x)
def _layernorm(x, axis=-1, eps=1e-5):
    m = x.mean(dim=axis, keepdim=True)
    v = x.var(dim=axis, keepdim=True, unbiased=False)
    return (x - m) / torch.sqrt(v + eps)
def _scatter_add(tgt, idx, src, axis=0):
    return tgt.clone().index_add_(axis, idx, src)
def _segment_sum(src, seg, n):
    out = torch.zeros((n,) + src.shape[1:], dtype=src.dtype)
    return out.index_add_(0, seg, src)
def _pad(x, pw):
    flat = tuple(v for pair in reversed(pw) for v in pair)
    return torch.nn.functional.pad(x, flat)

kernel_name = 'concat_heads__mha_block_cached__mha_block_cached__near_ridge'

def setup_inputs():

    _w = (lambda a: (lambda t: t.to(torch.bfloat16) if t.is_floating_point() else t)(torch.as_tensor(a)))
    def _A_setup():
        B, Sq, D = 8, 96, 640
        H, Sk, Dh = 32, 512, 192
        return {
            "x": _w((lambda *s: torch.randn(*s, dtype=torch.bfloat16) * 0.8)(B, Sq, D)),
            "k_cache": _w((lambda *s: torch.randn(*s, dtype=torch.bfloat16) * 0.8)(B, H, Sk, Dh)),
            "v_cache": _w((lambda *s: torch.randn(*s, dtype=torch.bfloat16) * 0.05)(B, H, Sk, Dh)),
            "wq": _w((lambda *s: torch.randn(*s, dtype=torch.bfloat16) * 0.8)(D, H * Dh) * (D ** -0.5)),
            "wo": _w((lambda *s: torch.randn(*s, dtype=torch.bfloat16) * 0.05)(H * Dh, D) * ((H * Dh) ** -0.5)),
        }
    _A_in = _A_setup()

    def _B_setup():
        B, Sq, D = 8, 96, 640
        H, Sk, Dh = 32, 512, 192
        return {
            "x": _w((lambda *s: torch.randn(*s, dtype=torch.bfloat16) * 0.8)(B, Sq, D)),
            "k_cache": _w((lambda *s: torch.randn(*s, dtype=torch.bfloat16) * 0.8)(B, H, Sk, Dh)),
            "v_cache": _w((lambda *s: torch.randn(*s, dtype=torch.bfloat16) * 0.05)(B, H, Sk, Dh)),
            "wq": _w((lambda *s: torch.randn(*s, dtype=torch.bfloat16) * 0.8)(D, H * Dh) * (D ** -0.5)),
            "wo": _w((lambda *s: torch.randn(*s, dtype=torch.bfloat16) * 0.05)(H * Dh, D) * ((H * Dh) ** -0.5)),
        }
    _B_in = _B_setup()

    return {
        "A_x": _A_in["x"],
        "A_k_cache": _A_in["k_cache"],
        "A_v_cache": _A_in["v_cache"],
        "A_wq": _A_in["wq"],
        "A_wo": _A_in["wo"],
        "B_x": _B_in["x"],
        "B_k_cache": _B_in["k_cache"],
        "B_v_cache": _B_in["v_cache"],
        "B_wq": _B_in["wq"],
        "B_wo": _B_in["wo"],
    }

def reference(A_x, A_k_cache, A_v_cache, A_wq, A_wo, B_x, B_k_cache, B_v_cache, B_wq, B_wo):
    def _A_ref(x, k_cache, v_cache, wq, wo):
        B, Sq, D = x.shape
        H, Dh = 32, 192
        q = (lambda x, *d: x.permute(*d))((x @ wq).reshape(B, Sq, H, Dh), 0, 2, 1, 3)
        scores = torch.einsum("bhqd,bhkd->bhqk", q, k_cache) * (Dh ** -0.5)
        p = _softmax(scores, axis=-1)
        o = torch.einsum("bhqk,bhkd->bhqd", p, v_cache)
        return (lambda x, *d: x.permute(*d))(o, 0, 2, 1, 3).reshape(B, Sq, H * Dh) @ wo

    def _B_ref(x, k_cache, v_cache, wq, wo):
        B, Sq, D = x.shape
        H, Dh = 32, 192
        q = (lambda x, *d: x.permute(*d))((x @ wq).reshape(B, Sq, H, Dh), 0, 2, 1, 3)
        scores = torch.einsum("bhqd,bhkd->bhqk", q, k_cache) * (Dh ** -0.5)
        p = _softmax(scores, axis=-1)
        o = torch.einsum("bhqk,bhkd->bhqd", p, v_cache)
        return (lambda x, *d: x.permute(*d))(o, 0, 2, 1, 3).reshape(B, Sq, H * Dh) @ wo

    a = _A_ref(A_x, A_k_cache, A_v_cache, A_wq, A_wo)
    b = _B_ref(B_x, B_k_cache, B_v_cache, B_wq, B_wo)
    return torch.concatenate([a, b], axis=-1)
```

```cpp
#include <cuda_runtime.h>
#include <cuda_bf16.h>
#include <cuda.h>
#include <stdint.h>

namespace {

constexpr int NB = 8, SQ = 96, DM = 640, NH = 32, SK = 512, DH = 192;
constexpr int SLOT = 24576;
constexpr int NSLOT = 8;
constexpr int SMEM_BYTES = NSLOT * SLOT + SLOT   + 1024   + 256  ;

#define NCTA 132
#define NPAIR 224
#define NH_TAIL 2
#define O_LIMIT 0
#define FETCH_AHEAD 3
#define N_ATT 66
constexpr int N_TICKETS = NPAIR + 2 * (256 - NPAIR) + (NCTA - N_ATT) / 2;
#define N_TAILG 8
#define MIDPAIR 0
#define G8 20
#define G4 28
#define NCH_A 4
#define NCH_B 4
constexpr int N_OTASKS = (NCH_A + NCH_B) * 20;

struct Maps { CUtensorMap x[2], x1[2], wq[2], k[2], v[2], wo[2]; const uint8_t* wop[2]; const uint8_t* kp[2]; const uint8_t* vp[2]; };
#define KV_INFLIGHT 8
#define WQ_EF 1
#define NRED 24
#define O_DEDICATED 0
#define PFQ 0
#define PFQ_DELAY 1500
#define PFQ_FIRST 0
#define WO_PF 0

__device__ uint4 g_stash[2 * NH * NB * 2304];
__device__ float4 g_part[2 * 4 * 5 * 2 * 24 * 128];
__device__ unsigned int g_tile_cnt[2 * 4 * 5 * 8];
__device__ unsigned int g_flag[2 * NB * NH];
__device__ unsigned int g_grp[32];
__device__ unsigned int g_ticket, g_oticket, g_oactive, g_done;

#define STAMP(i, tk)
#define FINE(k)

__device__ __forceinline__ uint32_t smem_u32(const void* p) { return (uint32_t)__cvta_generic_to_shared(p); }
__device__ __forceinline__ void mbar_init(uint32_t bar, int cnt) { asm volatile("mbarrier.init.shared::cta.b64 [%0], %1;" :: "r"(bar), "r"(cnt) : "memory"); }
__device__ __forceinline__ void mbar_expect_tx(uint32_t bar, uint32_t bytes) { asm volatile("mbarrier.arrive.expect_tx.shared::cta.b64 _, [%0], %1;" :: "r"(bar), "r"(bytes) : "memory"); }
__device__ __forceinline__ void mbar_arrive(uint32_t bar) { asm volatile("mbarrier.arrive.shared::cta.b64 _, [%0];" :: "r"(bar) : "memory"); }
__device__ __forceinline__ void mbar_wait(uint32_t bar, uint32_t parity) {
  asm volatile("{\n.reg .pred p;\nWAIT_%=:\nmbarrier.try_wait.parity.shared::cta.b64 p, [%0], %1;\n@p bra DONE_%=;\nbra WAIT_%=;\nDONE_%=:\n}" :: "r"(bar), "r"(parity) : "memory");
}
__device__ __forceinline__ bool mbar_test(uint32_t bar, uint32_t parity) {
  uint32_t ok;
  asm volatile("{\n.reg .pred p;\nmbarrier.test_wait.parity.shared::cta.b64 p, [%1], %2;\nselp.u32 %0, 1, 0, p;\n}" : "=r"(ok) : "r"(bar), "r"(parity) : "memory");
  return __all_sync(0xffffffffu, ok != 0);
}
__device__ __forceinline__ void tma_2d(uint32_t dst, const CUtensorMap* m, int c0, int c1, uint32_t bar) {
  asm volatile("cp.async.bulk.tensor.2d.shared::cluster.global.mbarrier::complete_tx::bytes [%0], [%1, {%3, %4}], [%2];"
               :: "r"(dst), "l"(m), "r"(bar), "r"(c0), "r"(c1) : "memory");
}
__device__ __forceinline__ void tma_3d(uint32_t dst, const CUtensorMap* m, int c0, int c1, int c2, uint32_t bar) {
  asm volatile("cp.async.bulk.tensor.3d.shared::cluster.global.mbarrier::complete_tx::bytes [%0], [%1, {%3, %4, %5}], [%2];"
               :: "r"(dst), "l"(m), "r"(bar), "r"(c0), "r"(c1), "r"(c2) : "memory");
}
__device__ __forceinline__ void tma_3d_hint(uint32_t dst, const CUtensorMap* m, int c0, int c1, int c2, uint32_t bar, uint64_t pol) {
  asm volatile("cp.async.bulk.tensor.3d.shared::cluster.global.mbarrier::complete_tx::bytes.L2::cache_hint [%0], [%1, {%3, %4, %5}], [%2], %6;"
               :: "r"(dst), "l"(m), "r"(bar), "r"(c0), "r"(c1), "r"(c2), "l"(pol) : "memory");
}
__device__ __forceinline__ void tma_4d(uint32_t dst, const CUtensorMap* m, int c2, int c3, uint32_t bar) {
  asm volatile("cp.async.bulk.tensor.4d.shared::cluster.global.mbarrier::complete_tx::bytes [%0], [%1, {%3, %3, %4, %5}], [%2];"
               :: "r"(dst), "l"(m), "r"(bar), "r"(0), "r"(c2), "r"(c3) : "memory");
}
__device__ __forceinline__ void tma_4d_hint(uint32_t dst, const CUtensorMap* m, int c2, int c3, uint32_t bar, uint64_t pol) {
  asm volatile("cp.async.bulk.tensor.4d.shared::cluster.global.mbarrier::complete_tx::bytes.L2::cache_hint [%0], [%1, {%3, %3, %4, %5}], [%2], %6;"
               :: "r"(dst), "l"(m), "r"(bar), "r"(0), "r"(c2), "r"(c3), "l"(pol) : "memory");
}
__device__ __forceinline__ void bulk_load(uint32_t dst, const void* src, uint32_t bytes, uint32_t bar) {
  asm volatile("cp.async.bulk.shared::cluster.global.mbarrier::complete_tx::bytes [%0], [%1], %2, [%3];" :: "r"(dst), "l"(src), "r"(bytes), "r"(bar) : "memory");
}
__device__ __forceinline__ void wg_fence() { asm volatile("wgmma.fence.sync.aligned;" ::: "memory"); }
__device__ __forceinline__ void wg_commit() { asm volatile("wgmma.commit_group.sync.aligned;" ::: "memory"); }
template <int N> __device__ __forceinline__ void wg_wait() { asm volatile("wgmma.wait_group.sync.aligned %0;" :: "n"(N) : "memory"); }
template <int N> __device__ __forceinline__ void touch(float (&d)[N]) {
#pragma unroll
  for (int i = 0; i < N; i++) asm volatile("" : "+f"(d[i]) :: "memory");
}
template <int N> __device__ __forceinline__ void touch_u(uint32_t (&d)[N]) {
#pragma unroll
  for (int i = 0; i < N; i++) asm volatile("" : "+r"(d[i]) :: "memory");
}
__device__ __forceinline__ float ex2(float x) { float y; asm("ex2.approx.ftz.f32 %0, %1;" : "=f"(y) : "f"(x)); return y; }
__device__ __forceinline__ float ex2v(float x) { float y; asm volatile("ex2.approx.ftz.f32 %0, %1;" : "=f"(y) : "f"(x)); return y; }
__device__ __forceinline__ void mulv(float& x, float a) { asm volatile("mul.f32 %0, %0, %1;" : "+f"(x) : "f"(a)); }
__device__ __forceinline__ uint32_t pack_bf16(float lo, float hi) { uint32_t r; asm("cvt.rn.bf16x2.f32 %0, %1, %2;" : "=r"(r) : "f"(hi), "f"(lo)); return r; }

constexpr uint64_t DESC_SW128 = (uint64_t)1 << 62;
__device__ __forceinline__ uint64_t desc_kmajor_sw128(uint32_t addr) {
  return DESC_SW128 | ((uint64_t)(1024 >> 4) << 32) | ((uint64_t)1 << 16) | (uint64_t)((addr & 0x3FFFF) >> 4);
}
__device__ __forceinline__ uint64_t desc_k_il(uint32_t addr) {
  return DESC_SW128 | ((uint64_t)(3072 >> 4) << 32) | ((uint64_t)1 << 16) | (uint64_t)((addr & 0x3FFFF) >> 4);
}
__device__ __forceinline__ uint64_t desc_mn_il(uint32_t addr) {
  return DESC_SW128 | ((uint64_t)(3072 >> 4) << 32) | ((uint64_t)(1024 >> 4) << 16) | (uint64_t)((addr & 0x3FFFF) >> 4);
}
template <int LBO> __device__ __forceinline__ uint64_t desc_mnmajor_sw128(uint32_t addr) {
  return DESC_SW128 | ((uint64_t)(1024 >> 4) << 32) | ((uint64_t)(LBO >> 4) << 16) | (uint64_t)((addr & 0x3FFFF) >> 4);
}
__device__ __forceinline__ uint64_t desc_kmajor_nosw(uint32_t addr) {
  return ((uint64_t)(1024 >> 4) << 32) | ((uint64_t)(128 >> 4) << 16) | (uint64_t)((addr & 0x3FFFF) >> 4);
}

__device__ __forceinline__ void wgmma_rs_n64_t0(float (&d)[32], uint32_t a0, uint32_t a1, uint32_t a2, uint32_t a3, uint64_t descB, int scaleD) {
  asm volatile("{\n.reg .pred p;\nsetp.ne.b32 p, %37, 0;\n"
    "wgmma.mma_async.sync.aligned.m64n64k16.f32.bf16.bf16 "
    "{%0, %1, %2, %3, %4, %5, %6, %7, %8, %9, %10, %11, %12, %13, %14, %15, %16, %17, %18, %19, %20, %21, %22, %23, %24, %25, %26, %27, %28, %29, %30, %31}, "
    "{%32, %33, %34, %35}, %36, p, 1, 1, 0;\n}\n"
    : "+f"(d[0]), "+f"(d[1]), "+f"(d[2]), "+f"(d[3]), "+f"(d[4]), "+f"(d[5]), "+f"(d[6]), "+f"(d[7]), "+f"(d[8]), "+f"(d[9]), "+f"(d[10]), "+f"(d[11]), "+f"(d[12]), "+f"(d[13]), "+f"(d[14]), "+f"(d[15]), "+f"(d[16]), "+f"(d[17]), "+f"(d[18]), "+f"(d[19]), "+f"(d[20]), "+f"(d[21]), "+f"(d[22]), "+f"(d[23]), "+f"(d[24]), "+f"(d[25]), "+f"(d[26]), "+f"(d[27]), "+f"(d[28]), "+f"(d[29]), "+f"(d[30]), "+f"(d[31])
    : "r"(a0), "r"(a1), "r"(a2), "r"(a3), "l"(descB), "r"(scaleD));
}
__device__ __forceinline__ void wgmma_rs_n192_t1(float (&d)[96], uint32_t a0, uint32_t a1, uint32_t a2, uint32_t a3, uint64_t descB, int scaleD) {
  asm volatile("{\n.reg .pred p;\nsetp.ne.b32 p, %101, 0;\n"
    "wgmma.mma_async.sync.aligned.m64n192k16.f32.bf16.bf16 "
    "{%0, %1, %2, %3, %4, %5, %6, %7, %8, %9, %10, %11, %12, %13, %14, %15, %16, %17, %18, %19, %20, %21, %22, %23, %24, %25, %26, %27, %28, %29, %30, %31, %32, %33, %34, %35, %36, %37, %38, %39, %40, %41, %42, %43, %44, %45, %46, %47, %48, %49, %50, %51, %52, %53, %54, %55, %56, %57, %58, %59, %60, %61, %62, %63, %64, %65, %66, %67, %68, %69, %70, %71, %72, %73, %74, %75, %76, %77, %78, %79, %80, %81, %82, %83, %84, %85, %86, %87, %88, %89, %90, %91, %92, %93, %94, %95}, "
    "{%96, %97, %98, %99}, %100, p, 1, 1, 1;\n}\n"
    : "+f"(d[0]), "+f"(d[1]), "+f"(d[2]), "+f"(d[3]), "+f"(d[4]), "+f"(d[5]), "+f"(d[6]), "+f"(d[7]), "+f"(d[8]), "+f"(d[9]), "+f"(d[10]), "+f"(d[11]), "+f"(d[12]), "+f"(d[13]), "+f"(d[14]), "+f"(d[15]), "+f"(d[16]), "+f"(d[17]), "+f"(d[18]), "+f"(d[19]), "+f"(d[20]), "+f"(d[21]), "+f"(d[22]), "+f"(d[23]), "+f"(d[24]), "+f"(d[25]), "+f"(d[26]), "+f"(d[27]), "+f"(d[28]), "+f"(d[29]), "+f"(d[30]), "+f"(d[31]), "+f"(d[32]), "+f"(d[33]), "+f"(d[34]), "+f"(d[35]), "+f"(d[36]), "+f"(d[37]), "+f"(d[38]), "+f"(d[39]), "+f"(d[40]), "+f"(d[41]), "+f"(d[42]), "+f"(d[43]), "+f"(d[44]), "+f"(d[45]), "+f"(d[46]), "+f"(d[47]), "+f"(d[48]), "+f"(d[49]), "+f"(d[50]), "+f"(d[51]), "+f"(d[52]), "+f"(d[53]), "+f"(d[54]), "+f"(d[55]), "+f"(d[56]), "+f"(d[57]), "+f"(d[58]), "+f"(d[59]), "+f"(d[60]), "+f"(d[61]), "+f"(d[62]), "+f"(d[63]), "+f"(d[64]), "+f"(d[65]), "+f"(d[66]), "+f"(d[67]), "+f"(d[68]), "+f"(d[69]), "+f"(d[70]), "+f"(d[71]), "+f"(d[72]), "+f"(d[73]), "+f"(d[74]), "+f"(d[75]), "+f"(d[76]), "+f"(d[77]), "+f"(d[78]), "+f"(d[79]), "+f"(d[80]), "+f"(d[81]), "+f"(d[82]), "+f"(d[83]), "+f"(d[84]), "+f"(d[85]), "+f"(d[86]), "+f"(d[87]), "+f"(d[88]), "+f"(d[89]), "+f"(d[90]), "+f"(d[91]), "+f"(d[92]), "+f"(d[93]), "+f"(d[94]), "+f"(d[95])
    : "r"(a0), "r"(a1), "r"(a2), "r"(a3), "l"(descB), "r"(scaleD));
}
__device__ __forceinline__ void wgmma_ss_n192_t1(float (&d)[96], uint64_t descA, uint64_t descB, int scaleD) {
  asm volatile("{\n.reg .pred p;\nsetp.ne.b32 p, %98, 0;\n"
    "wgmma.mma_async.sync.aligned.m64n192k16.f32.bf16.bf16 "
    "{%0, %1, %2, %3, %4, %5, %6, %7, %8, %9, %10, %11, %12, %13, %14, %15, %16, %17, %18, %19, %20, %21, %22, %23, %24, %25, %26, %27, %28, %29, %30, %31, %32, %33, %34, %35, %36, %37, %38, %39, %40, %41, %42, %43, %44, %45, %46, %47, %48, %49, %50, %51, %52, %53, %54, %55, %56, %57, %58, %59, %60, %61, %62, %63, %64, %65, %66, %67, %68, %69, %70, %71, %72, %73, %74, %75, %76, %77, %78, %79, %80, %81, %82, %83, %84, %85, %86, %87, %88, %89, %90, %91, %92, %93, %94, %95}, "
    "%96, %97, p, 1, 1, 0, 1;\n}\n"
    : "+f"(d[0]), "+f"(d[1]), "+f"(d[2]), "+f"(d[3]), "+f"(d[4]), "+f"(d[5]), "+f"(d[6]), "+f"(d[7]), "+f"(d[8]), "+f"(d[9]), "+f"(d[10]), "+f"(d[11]), "+f"(d[12]), "+f"(d[13]), "+f"(d[14]), "+f"(d[15]), "+f"(d[16]), "+f"(d[17]), "+f"(d[18]), "+f"(d[19]), "+f"(d[20]), "+f"(d[21]), "+f"(d[22]), "+f"(d[23]), "+f"(d[24]), "+f"(d[25]), "+f"(d[26]), "+f"(d[27]), "+f"(d[28]), "+f"(d[29]), "+f"(d[30]), "+f"(d[31]), "+f"(d[32]), "+f"(d[33]), "+f"(d[34]), "+f"(d[35]), "+f"(d[36]), "+f"(d[37]), "+f"(d[38]), "+f"(d[39]), "+f"(d[40]), "+f"(d[41]), "+f"(d[42]), "+f"(d[43]), "+f"(d[44]), "+f"(d[45]), "+f"(d[46]), "+f"(d[47]), "+f"(d[48]), "+f"(d[49]), "+f"(d[50]), "+f"(d[51]), "+f"(d[52]), "+f"(d[53]), "+f"(d[54]), "+f"(d[55]), "+f"(d[56]), "+f"(d[57]), "+f"(d[58]), "+f"(d[59]), "+f"(d[60]), "+f"(d[61]), "+f"(d[62]), "+f"(d[63]), "+f"(d[64]), "+f"(d[65]), "+f"(d[66]), "+f"(d[67]), "+f"(d[68]), "+f"(d[69]), "+f"(d[70]), "+f"(d[71]), "+f"(d[72]), "+f"(d[73]), "+f"(d[74]), "+f"(d[75]), "+f"(d[76]), "+f"(d[77]), "+f"(d[78]), "+f"(d[79]), "+f"(d[80]), "+f"(d[81]), "+f"(d[82]), "+f"(d[83]), "+f"(d[84]), "+f"(d[85]), "+f"(d[86]), "+f"(d[87]), "+f"(d[88]), "+f"(d[89]), "+f"(d[90]), "+f"(d[91]), "+f"(d[92]), "+f"(d[93]), "+f"(d[94]), "+f"(d[95])
    : "l"(descA), "l"(descB), "r"(scaleD));
}
__device__ __forceinline__ void wgmma_ss_n64_t1(float (&d)[32], uint64_t descA, uint64_t descB, int scaleD) {
  asm volatile("{\n.reg .pred p;\nsetp.ne.b32 p, %34, 0;\n"
    "wgmma.mma_async.sync.aligned.m64n64k16.f32.bf16.bf16 "
    "{%0, %1, %2, %3, %4, %5, %6, %7, %8, %9, %10, %11, %12, %13, %14, %15, %16, %17, %18, %19, %20, %21, %22, %23, %24, %25, %26, %27, %28, %29, %30, %31}, "
    "%32, %33, p, 1, 1, 0, 1;\n}\n"
    : "+f"(d[0]), "+f"(d[1]), "+f"(d[2]), "+f"(d[3]), "+f"(d[4]), "+f"(d[5]), "+f"(d[6]), "+f"(d[7]), "+f"(d[8]), "+f"(d[9]), "+f"(d[10]), "+f"(d[11]), "+f"(d[12]), "+f"(d[13]), "+f"(d[14]), "+f"(d[15]), "+f"(d[16]), "+f"(d[17]), "+f"(d[18]), "+f"(d[19]), "+f"(d[20]), "+f"(d[21]), "+f"(d[22]), "+f"(d[23]), "+f"(d[24]), "+f"(d[25]), "+f"(d[26]), "+f"(d[27]), "+f"(d[28]), "+f"(d[29]), "+f"(d[30]), "+f"(d[31])
    : "l"(descA), "l"(descB), "r"(scaleD));
}
__device__ __forceinline__ void wgmma_ss_n32_t1(float (&d)[16], uint64_t descA, uint64_t descB, int scaleD) {
  asm volatile("{\n.reg .pred p;\nsetp.ne.b32 p, %18, 0;\n"
    "wgmma.mma_async.sync.aligned.m64n32k16.f32.bf16.bf16 "
    "{%0, %1, %2, %3, %4, %5, %6, %7, %8, %9, %10, %11, %12, %13, %14, %15}, "
    "%16, %17, p, 1, 1, 0, 1;\n}\n"
    : "+f"(d[0]), "+f"(d[1]), "+f"(d[2]), "+f"(d[3]), "+f"(d[4]), "+f"(d[5]), "+f"(d[6]), "+f"(d[7]), "+f"(d[8]), "+f"(d[9]), "+f"(d[10]), "+f"(d[11]), "+f"(d[12]), "+f"(d[13]), "+f"(d[14]), "+f"(d[15])
    : "l"(descA), "l"(descB), "r"(scaleD));
}
__device__ __forceinline__ void wgmma_st_n192_t0(float (&d)[96], uint64_t descA, uint64_t descB, int scaleD) {
  asm volatile("{\n.reg .pred p;\nsetp.ne.b32 p, %98, 0;\n"
    "wgmma.mma_async.sync.aligned.m64n192k16.f32.bf16.bf16 "
    "{%0, %1, %2, %3, %4, %5, %6, %7, %8, %9, %10, %11, %12, %13, %14, %15, %16, %17, %18, %19, %20, %21, %22, %23, %24, %25, %26, %27, %28, %29, %30, %31, %32, %33, %34, %35, %36, %37, %38, %39, %40, %41, %42, %43, %44, %45, %46, %47, %48, %49, %50, %51, %52, %53, %54, %55, %56, %57, %58, %59, %60, %61, %62, %63, %64, %65, %66, %67, %68, %69, %70, %71, %72, %73, %74, %75, %76, %77, %78, %79, %80, %81, %82, %83, %84, %85, %86, %87, %88, %89, %90, %91, %92, %93, %94, %95}, "
    "%96, %97, p, 1, 1, 1, 0;\n}\n"
    : "+f"(d[0]), "+f"(d[1]), "+f"(d[2]), "+f"(d[3]), "+f"(d[4]), "+f"(d[5]), "+f"(d[6]), "+f"(d[7]), "+f"(d[8]), "+f"(d[9]), "+f"(d[10]), "+f"(d[11]), "+f"(d[12]), "+f"(d[13]), "+f"(d[14]), "+f"(d[15]), "+f"(d[16]), "+f"(d[17]), "+f"(d[18]), "+f"(d[19]), "+f"(d[20]), "+f"(d[21]), "+f"(d[22]), "+f"(d[23]), "+f"(d[24]), "+f"(d[25]), "+f"(d[26]), "+f"(d[27]), "+f"(d[28]), "+f"(d[29]), "+f"(d[30]), "+f"(d[31]), "+f"(d[32]), "+f"(d[33]), "+f"(d[34]), "+f"(d[35]), "+f"(d[36]), "+f"(d[37]), "+f"(d[38]), "+f"(d[39]), "+f"(d[40]), "+f"(d[41]), "+f"(d[42]), "+f"(d[43]), "+f"(d[44]), "+f"(d[45]), "+f"(d[46]), "+f"(d[47]), "+f"(d[48]), "+f"(d[49]), "+f"(d[50]), "+f"(d[51]), "+f"(d[52]), "+f"(d[53]), "+f"(d[54]), "+f"(d[55]), "+f"(d[56]), "+f"(d[57]), "+f"(d[58]), "+f"(d[59]), "+f"(d[60]), "+f"(d[61]), "+f"(d[62]), "+f"(d[63]), "+f"(d[64]), "+f"(d[65]), "+f"(d[66]), "+f"(d[67]), "+f"(d[68]), "+f"(d[69]), "+f"(d[70]), "+f"(d[71]), "+f"(d[72]), "+f"(d[73]), "+f"(d[74]), "+f"(d[75]), "+f"(d[76]), "+f"(d[77]), "+f"(d[78]), "+f"(d[79]), "+f"(d[80]), "+f"(d[81]), "+f"(d[82]), "+f"(d[83]), "+f"(d[84]), "+f"(d[85]), "+f"(d[86]), "+f"(d[87]), "+f"(d[88]), "+f"(d[89]), "+f"(d[90]), "+f"(d[91]), "+f"(d[92]), "+f"(d[93]), "+f"(d[94]), "+f"(d[95])
    : "l"(descA), "l"(descB), "r"(scaleD));
}

struct Cons {
  uint32_t base, full0;
  uint32_t it;
  int lane;
  __device__ __forceinline__ uint32_t wait(uint32_t slot, uint32_t u) const { mbar_wait(full0 + slot * 8, (u >> 3) & 1); return base + slot * SLOT; }
  __device__ __forceinline__ uint32_t wait(uint32_t u) const { return wait(u & 7, u); }
  __device__ __forceinline__ void release(uint32_t slot) const { if (lane == 0) mbar_arrive(full0 + 64 + (slot & 7) * 8); }
};

__device__ __forceinline__ int ticket_task(int ticket) {
  int u = ticket, f = 0;
  if (ticket >= N_ATT) {
    if (ticket < NCTA) { const int s = ticket - N_ATT; u = N_ATT + (s >> 1); f = 1 | ((s & 1) << 2); }
    else {
      u = ticket - (NCTA - N_ATT) / 2;
      if (u >= NPAIR) { const int s = u - NPAIR; u = NPAIR + (s >> 1); f = 1 | ((s & 1) << 2); }
    }
  }
  const int hh = u & 7, pr = (u >> 3) & 3, g = (u >> 5) & 3, blk = u >> 7;
  return f | (pr << 3) | ((g * 8 + hh) << 5) | (blk << 10);
}
__device__ __forceinline__ int o_task(int i) {
  const int blk = i >= NCH_A * 20, nch = blk ? NCH_B : NCH_A;
  if (blk) i -= NCH_A * 20;
  const int c = i / 20, r = i - c * 20, pr = r / 5, nt = r - pr * 5;
  const int h0 = (c * NH) / nch, h1 = ((c + 1) * NH) / nch;
  return 3 | (nt << 2) | (pr << 5) | (blk << 7) | (h0 << 8) | ((h1 - h0) << 13);
}

__device__ __forceinline__ void qproj(Cons& r, uint32_t (&qf)[48], uint32_t park, bool pair, int wg, int tid) {
  float acc[96];
  float acx[32];
  float acy[16];
  for (int c = 0; c < 10; c++) {
    const uint32_t sx = r.it;
    const uint32_t xa = r.wait(sx), wa = r.wait(sx + 1);
    const uint64_t da = desc_kmajor_sw128(xa + wg * 8192), d2 = desc_kmajor_sw128(xa + 2 * 8192);
    const uint64_t db = desc_mn_il(wa), dbx = desc_mn_il(wa + wg * 1024), dby = desc_mn_il(wa + 2048 + wg * 64);
    wg_fence();
    if (pair) {
#pragma unroll
      for (int ks = 0; ks < 4; ks++) {
        const int sc = (c > 0 || ks > 0) ? 1 : 0;
        wgmma_ss_n192_t1(acc, da + ks * 2, db + ks * 384, sc);
        wgmma_ss_n64_t1(acx, d2 + ks * 2, dbx + ks * 384, sc);
        wgmma_ss_n32_t1(acy, d2 + ks * 2, dby + ks * 384, sc);
      }
    } else {
#pragma unroll
      for (int ks = 0; ks < 4; ks++)
        wgmma_ss_n192_t1(acc, da + ks * 2, db + ks * 384, (c > 0 || ks > 0) ? 1 : 0);
    }
    wg_commit();
    if (c > 0) { wg_wait<1>(); r.release((sx + 6) & 7); r.release((sx + 7) & 7); }
    r.it += 2;
  }
  wg_wait<0>();
  touch(acc); touch(acx); touch(acy);
  r.release((r.it + 6) & 7); r.release((r.it + 7) & 7);
  if (pair) {
#pragma unroll
    for (int ks = 0; ks < 4; ks++) {
      uint32_t a0 = pack_bf16(acx[8 * ks + 0], acx[8 * ks + 1]), a1 = pack_bf16(acx[8 * ks + 2], acx[8 * ks + 3]);
      uint32_t a2 = pack_bf16(acx[8 * ks + 4], acx[8 * ks + 5]), a3 = pack_bf16(acx[8 * ks + 6], acx[8 * ks + 7]);
      asm volatile("st.shared.v4.b32 [%0], {%1, %2, %3, %4};" :: "r"(park + ((wg * 4 + ks) * 128 + tid) * 16), "r"(a0), "r"(a1), "r"(a2), "r"(a3) : "memory");
    }
#pragma unroll
    for (int ks = 0; ks < 2; ks++) {
      uint32_t a0 = pack_bf16(acy[8 * ks + 0], acy[8 * ks + 1]), a1 = pack_bf16(acy[8 * ks + 2], acy[8 * ks + 3]);
      uint32_t a2 = pack_bf16(acy[8 * ks + 4], acy[8 * ks + 5]), a3 = pack_bf16(acy[8 * ks + 6], acy[8 * ks + 7]);
      asm volatile("st.shared.v4.b32 [%0], {%1, %2, %3, %4};" :: "r"(park + ((8 + wg * 2 + ks) * 128 + tid) * 16), "r"(a0), "r"(a1), "r"(a2), "r"(a3) : "memory");
    }
  }
#pragma unroll
  for (int i = 0; i < 48; i++) qf[i] = pack_bf16(acc[2 * i], acc[2 * i + 1]);
}

__device__ __forceinline__ void sched_sync(int wg) { asm volatile("bar.sync %0, 256;" :: "r"(2 + wg) : "memory"); }
__device__ __forceinline__ void sched_arrive(int wg) { asm volatile("bar.arrive %0, 256;" :: "r"(3 - wg) : "memory"); }

__device__ __forceinline__ void issue_qk(float (&s)[32], const uint32_t (&qf)[48], uint64_t dk) {
#pragma unroll
  for (int ks = 0; ks < 12; ks++)
    wgmma_rs_n64_t0(s, qf[4 * ks], qf[4 * ks + 1], qf[4 * ks + 2], qf[4 * ks + 3], dk + ((ks >> 2) * 64 + (ks & 3) * 2), ks > 0);
  wg_commit();
}
__device__ __forceinline__ void attention(Cons& r, const uint32_t (&qf)[48], bool valid, uint32_t* dst, uint32_t sig, int wg) {
  constexpr float CS = 0.07216878364870322f * 1.4426950408889634f;
  const int lane = r.lane;
  float o[96];
  float s[32];
  uint32_t pa[8], pb[8];
  float m0 = -INFINITY, m1 = -INFINITY, l0 = 0.f, l1 = 0.f, al0 = 1.f, al1 = 1.f;
  bool resc = false;
#pragma unroll
  for (int i = 0; i < 8; i++) { pa[i] = 0; pb[i] = 0; }

  auto row_max = [&]() {
    float x0 = fmaxf(s[0], s[1]), x1 = fmaxf(s[2], s[3]), y0 = fmaxf(s[4], s[5]), y1 = fmaxf(s[6], s[7]);
#pragma unroll
    for (int i = 2; i < 8; i += 2) {
      x0 = fmaxf(x0, fmaxf(s[4 * i], s[4 * i + 1])); x1 = fmaxf(x1, fmaxf(s[4 * i + 2], s[4 * i + 3]));
      y0 = fmaxf(y0, fmaxf(s[4 * i + 4], s[4 * i + 5])); y1 = fmaxf(y1, fmaxf(s[4 * i + 6], s[4 * i + 7]));
    }
    x0 = fmaxf(x0, y0); x1 = fmaxf(x1, y1);
    x0 = fmaxf(x0, __shfl_xor_sync(0xffffffffu, x0, 1)); x1 = fmaxf(x1, __shfl_xor_sync(0xffffffffu, x1, 1));
    x0 = fmaxf(x0, __shfl_xor_sync(0xffffffffu, x0, 2)); x1 = fmaxf(x1, __shfl_xor_sync(0xffffffffu, x1, 2));
    resc = __any_sync(0xffffffffu, (x0 - m0) * CS > 8.0f || (x1 - m1) * CS > 8.0f);
    if (resc) {
      const float n0 = fmaxf(m0, x0), n1 = fmaxf(m1, x1);
      al0 = ex2((m0 - n0) * CS); al1 = ex2((m1 - n1) * CS);
      m0 = n0; m1 = n1;
      l0 *= al0; l1 *= al1;
    }
  };
  auto exps = [&](uint32_t (&p)[8], int h) {
    const float c0 = m0 * CS, c1 = m1 * CS;
    float t0 = 0.f, t1 = 0.f;
#pragma unroll
    for (int i = 0; i < 4; i++) {
      const int k = 16 * h + 4 * i;
      const float e0 = ex2(fmaf(s[k], CS, -c0)), e1 = ex2(fmaf(s[k + 1], CS, -c0));
      const float e2 = ex2(fmaf(s[k + 2], CS, -c1)), e3 = ex2(fmaf(s[k + 3], CS, -c1));
      t0 += e0 + e1; t1 += e2 + e3;
      p[2 * i] = pack_bf16(e0, e1); p[2 * i + 1] = pack_bf16(e2, e3);
    }
    l0 += t0; l1 += t1;
  };
  auto pv_a = [&](uint64_t dv, int first) {
    wgmma_rs_n192_t1(o, pa[0], pa[1], pa[2], pa[3], dv, first ? 0 : 1);
    wgmma_rs_n192_t1(o, pa[4], pa[5], pa[6], pa[7], dv + 384, 1);
    wg_commit();
  };
  auto pv_b = [&](uint64_t dv) {
    wgmma_rs_n192_t1(o, pb[0], pb[1], pb[2], pb[3], dv + 768, 1);
    wgmma_rs_n192_t1(o, pb[4], pb[5], pb[6], pb[7], dv + 1152, 1);
    wg_commit();
  };

  if (wg == 1) sched_arrive(1);
  {
    const uint32_t sk = r.it & 7;
    const uint64_t dk = desc_k_il(r.wait(sk, r.it));
    sched_sync(wg);
    wg_fence();
    issue_qk(s, qf, dk);
    sched_arrive(wg);
    wg_wait<0>();
    touch(s);
    r.release(sk);
    if (valid) { row_max(); exps(pa, 0); exps(pb, 1); }
  }
  for (int j = 0; j < 7; j++) {
    const uint32_t u = r.it;
    const uint32_t sv = (u + 1) & 7, sk = (u + 2) & 7;
    const uint64_t dk = desc_k_il(r.wait(sk, u + 2));
    const uint64_t dv = desc_mn_il(r.wait(sv, u + 1));

    FINE(0);
    sched_sync(wg);
    FINE(1);
    wg_fence();
    issue_qk(s, qf, dk);
    pv_a(dv, j == 0);
    pv_b(dv);
    FINE(3);
    sched_arrive(wg);
    wg_wait<2>();
    touch(s);
    FINE(4);
    r.release(sk);
    if (valid) row_max();
    wg_wait<1>();
    touch_u(pa);
    if (valid) exps(pa, 0);
    touch_u(pa);
    FINE(5);
    wg_wait<0>();
    touch(o); touch_u(pb);
    r.release(sv);
    if (valid) exps(pb, 1);
    if (resc) {
#pragma unroll
      for (int i = 0; i < 24; i++) { o[4 * i] *= al0; o[4 * i + 1] *= al0; o[4 * i + 2] *= al1; o[4 * i + 3] *= al1; }
    }
    touch_u(pb);
    FINE(6);
    r.it += 2;
  }
  {
    const uint32_t sv = (r.it + 1) & 7;
    const uint64_t dv = desc_mn_il(r.wait(sv, r.it + 1));
    sched_sync(wg);
    wg_fence();
    pv_a(dv, 0);
    pv_b(dv);
    if (wg == 0) sched_arrive(0);
    wg_wait<0>();
    touch(o); touch_u(pa); touch_u(pb);
    r.release(sv);
    r.it += 2;
  }
  if (valid) {
    l0 += __shfl_xor_sync(0xffffffffu, l0, 1); l1 += __shfl_xor_sync(0xffffffffu, l1, 1);
    l0 += __shfl_xor_sync(0xffffffffu, l0, 2); l1 += __shfl_xor_sync(0xffffffffu, l1, 2);
    const float i0 = 1.0f / l0, i1 = 1.0f / l1;
#pragma unroll
    for (int kc = 0; kc < 24; kc++) {
      dst[(kc >> 3) * 3072 + (kc & 7) * 32 + lane] = pack_bf16(o[4 * kc] * i0, o[4 * kc + 1] * i0);
      dst[(kc >> 3) * 3072 + 256 + (kc & 7) * 32 + lane] = pack_bf16(o[4 * kc + 2] * i1, o[4 * kc + 3] * i1);
    }
    __syncwarp();
    if (lane == 0) mbar_arrive(sig);
  }
}

__device__ __forceinline__ void o_complete(int& dtask, __nv_bfloat16* out, int wg, int w, int tid, uint32_t stage = 0) {
  if (dtask < 0) return;
  const int task = dtask, lane = tid & 31;
  dtask = -1;
  const int nt = (task >> 2) & 7, rs = (task >> 5) & 3, blk = (task >> 7) & 1, nh = (task >> 13) & 31;
  const int tile = (blk * 4 + rs) * 5 + nt;
  __threadfence();
  __syncwarp();
  unsigned int last = 0;
  if (lane == 0) {
    unsigned int* cnt = &g_tile_cnt[(tile * 2 + wg) * 4 + w];
    last = (atomicAdd(cnt, (unsigned)nh) + nh == NH);
    if (last) *cnt = 0;
  }
  if (__shfl_sync(0xffffffffu, last, 0)) {
    __threadfence();
    float4* part = g_part + (size_t)(tile * 2 + wg) * 24 * 128 + tid;
    const int c = nt * 128 + wg * 64 + w * 16 + (lane >> 2), q = lane & 3;
    const bool odd = (lane >> 2) & 1;
    __nv_bfloat16* o0 = out + (size_t)(rs * 192 + 2 * q + (odd ? 1 : 0)) * (2 * DM) + blk * DM + (c & ~1);
    if (stage) {
      stage += (wg * 24 * 128 + tid) * 16;
#pragma unroll
      for (int j = 0; j < 24; j++) asm volatile("cp.async.cg.shared.global [%0], [%1], 16;" :: "r"(stage + j * 2048), "l"(part + j * 128) : "memory");
      asm volatile("cp.async.wait_all;" ::: "memory");
    }
#pragma unroll 1
    for (int j0 = 0; j0 < 24; j0 += 4) {
      float4 v[4];
      if (stage) {
#pragma unroll
        for (int j = 0; j < 4; j++) asm volatile("ld.shared.v4.f32 {%0, %1, %2, %3}, [%4];" : "=f"(v[j].x), "=f"(v[j].y), "=f"(v[j].z), "=f"(v[j].w) : "r"(stage + (j0 + j) * 2048) : "memory");
      } else {
#pragma unroll
        for (int j = 0; j < 4; j++) v[j] = __ldcg(part + (j0 + j) * 128);
      }
#pragma unroll
      for (int j = 0; j < 4; j++) {
        __stcg(part + (j0 + j) * 128, make_float4(0.f, 0.f, 0.f, 0.f));
        const float sx = odd ? v[j].x : v[j].y, sz = odd ? v[j].z : v[j].w;
        const float rx = __shfl_xor_sync(0xffffffffu, sx, 4), rz = __shfl_xor_sync(0xffffffffu, sz, 4);
        __nv_bfloat16* o1 = o0 + (size_t)(j0 + j) * 8 * (2 * DM);
        *reinterpret_cast<uint32_t*>(o1) = odd ? pack_bf16(rx, v[j].y) : pack_bf16(v[j].x, rx);
        *reinterpret_cast<uint32_t*>(o1 + 8) = odd ? pack_bf16(rz, v[j].w) : pack_bf16(v[j].z, rz);
      }
    }
  }
}

__device__ __forceinline__ void oproj(Cons& r, int task, int& dtask, __nv_bfloat16* out, int wg, int w, int tid) {
  const int nt = (task >> 2) & 7, rs = (task >> 5) & 3, blk = (task >> 7) & 1, nh = (task >> 13) & 31;
  float acc[96];
  if (dtask >= 0 && !mbar_test(r.full0 + ((r.it + 1) & 7) * 8, ((r.it + 1) >> 3) & 1)) o_complete(dtask, out, wg, w, tid);
  for (int hh = 0; hh < nh; hh++) {
    const uint32_t u = r.it;
    const uint64_t dw0 = desc_mnmajor_sw128<1024>(r.wait(u) + wg * 12288);
    const uint64_t do0 = desc_kmajor_nosw(r.wait(u + 1));
    wg_fence();
#pragma unroll
    for (int ks = 0; ks < 4; ks++) wgmma_st_n192_t0(acc, dw0 + ks * 128, do0 + ks * 16, (hh > 0 || ks > 0) ? 1 : 0);
    wg_commit();
    if (hh > 0) { wg_wait<1>(); r.release(u + 6); r.release(u + 7); }
    const uint64_t do1 = desc_kmajor_nosw(r.wait(u + 2));
    wgmma_st_n192_t0(acc, dw0 + 4 * 128, do1, 1);
    wgmma_st_n192_t0(acc, dw0 + 5 * 128, do1 + 16, 1);
    const uint64_t dw1 = desc_mnmajor_sw128<1024>(r.wait(u + 3) + wg * 12288);
    wgmma_st_n192_t0(acc, dw1, do1 + 32, 1);
    wgmma_st_n192_t0(acc, dw1 + 128, do1 + 48, 1);
    wg_commit();
    if (hh == 0) o_complete(dtask, out, wg, w, tid);
    wg_wait<1>(); r.release(u + 1);
    const uint64_t do2 = desc_kmajor_nosw(r.wait(u + 4));
#pragma unroll
    for (int ks = 0; ks < 4; ks++) wgmma_st_n192_t0(acc, dw1 + (2 + ks) * 128, do2 + ks * 16, 1);
    wg_commit();
    wg_wait<1>(); r.release(u); r.release(u + 2);
    r.it += 5;
  }
  wg_wait<0>();
  touch(acc);
  r.release(r.it + 6); r.release(r.it + 7);
  float4* part = g_part + (size_t)(((blk * 4 + rs) * 5 + nt) * 2 + wg) * 24 * 128 + tid;
#pragma unroll
  for (int j = 0; j < 24; j++)
    asm volatile("red.global.add.v4.f32 [%0], {%1, %2, %3, %4};" :: "l"(part + j * 128), "f"(acc[4 * j]), "f"(acc[4 * j + 1]), "f"(acc[4 * j + 2]), "f"(acc[4 * j + 3]) : "memory");
  dtask = task;
}

__device__ __forceinline__ unsigned int ld_acquire(const unsigned int* p) { unsigned int v; asm volatile("ld.acquire.gpu.global.u32 %0, [%1];" : "=r"(v) : "l"(p) : "memory"); return v; }
__device__ __forceinline__ unsigned int ld_relaxed(const unsigned int* p) { unsigned int v; asm volatile("ld.relaxed.gpu.global.u32 %0, [%1];" : "=r"(v) : "l"(p) : "memory"); return v; }

__device__ __forceinline__ bool o_ready(int task, int lane) {
  const int rs = (task >> 5) & 3, blk = (task >> 7) & 1, h0 = (task >> 8) & 31, nh = (task >> 13) & 31;
  bool ok = true;
  if (lane < 2 * nh) {
    const int b = rs * 2 + (lane >= nh ? 1 : 0), h = h0 + (lane >= nh ? lane - nh : lane);
    ok = ld_acquire(&g_flag[(blk * NB + b) * NH + h]) == 6u;
  }
  return __all_sync(0xffffffffu, ok);
}

__global__ void __launch_bounds__(384, 1) fused_kernel(const __grid_constant__ Maps maps, __nv_bfloat16* out) {
  extern __shared__ uint8_t smem_raw[];
  const uint32_t sbase = (smem_u32(smem_raw) + 1023u) & ~1023u;
  const uint32_t park = sbase + NSLOT * SLOT;
  const uint32_t bars = park + SLOT;
  const uint32_t full0 = bars, empty0 = bars + 64;
  const uint32_t tfull0 = bars + 128, tempty0 = bars + 160, tbox = bars + 192, sreq = bars + 208, sig = bars + 216;
  const int warp = __shfl_sync(0xffffffffu, threadIdx.x >> 5, 0), lane = threadIdx.x & 31;
  if (threadIdx.x == 0) {
    for (int i = 0; i < NSLOT; i++) { mbar_init(full0 + 8 * i, 1); mbar_init(empty0 + 8 * i, 8); }
    for (int i = 0; i < 4; i++) { mbar_init(tfull0 + 8 * i, 1); mbar_init(tempty0 + 8 * i, 11); }
    mbar_init(sreq, 1);
    mbar_init(sig, 6);
    asm volatile("fence.mbarrier_init.release.cluster;" ::: "memory");
  }
  __syncthreads();

  if (warp < 4) {
    asm volatile("setmaxnreg.dec.sync.aligned.u32 24;");
    if (warp == 0) {
      if (lane == 0) {
        uint64_t pol; asm volatile("createpolicy.fractional.L2::evict_first.b64 %0, 1.0;" : "=l"(pol));
        uint32_t u = 0;
        auto acquire = [&](uint32_t bytes) -> uint32_t {
          const uint32_t s = u & 7;
          mbar_wait(empty0 + 8 * s, ((u >> 3) & 1) ^ 1);
          mbar_expect_tx(full0 + 8 * s, bytes);
          u++;
          return s;
        };
        for (uint32_t n = 0;; n++) {
          int task;
          mbar_wait(tfull0 + 8 * (n & 3), (n >> 2) & 1);
          asm volatile("ld.shared.b32 %0, [%1];" : "=r"(task) : "r"(tbox + 4 * (n & 3)) : "memory");
          mbar_arrive(tempty0 + 8 * (n & 3));
          if (task < 0) break;
          const int type = task & 3;
          if (type != 3) {
            const int bsel = (task >> 2) & 1, pr = (task >> 3) & 3, h = (task >> 5) & 31, blk = (task >> 10) & 1;
            if (type != 2) {
              const CUtensorMap* mx = type ? &maps.x1[blk] : &maps.x[blk];
#pragma unroll 1
              for (int c = 0; c < 10; c++) {
                uint32_t s = acquire(type ? SLOT / 2 : SLOT);
                tma_2d(sbase + s * SLOT, mx, c * 64, pr * 192 + bsel * 96, full0 + 8 * s);
                s = acquire(SLOT);
                tma_4d_hint(sbase + s * SLOT, &maps.wq[blk], h * 3, c * 8, full0 + 8 * s, pol);
              }
            }
            int rg = (((pr * 2 + bsel) * NH + h) * SK) >> 3;
#pragma unroll 1
            for (int j = 0; j < 8; j++) {
              if (j == 8 - FETCH_AHEAD) mbar_arrive(sreq);
              if (KV_INFLIGHT < 8 && u >= KV_INFLIGHT) mbar_wait(full0 + 8 * ((u - KV_INFLIGHT) & 7), ((u - KV_INFLIGHT) >> 3) & 1);
              uint32_t s = acquire(SLOT);
              tma_4d_hint(sbase + s * SLOT, &maps.k[blk], 0, rg, full0 + 8 * s, pol);
              if (KV_INFLIGHT < 8 && u >= KV_INFLIGHT) mbar_wait(full0 + 8 * ((u - KV_INFLIGHT) & 7), ((u - KV_INFLIGHT) >> 3) & 1);
              s = acquire(SLOT);
              tma_4d_hint(sbase + s * SLOT, &maps.v[blk], 0, rg, full0 + 8 * s, pol);
              rg += 8;
            }
          } else {
            const int nt = (task >> 2) & 7, rs = (task >> 5) & 3, blk = (task >> 7) & 1, h0 = (task >> 8) & 31, nh = (task >> 13) & 31;
            asm volatile("fence.proxy.async;" ::: "memory");
            const uint8_t* src = reinterpret_cast<const uint8_t*>(g_stash) + (size_t)((blk * NH + h0) * NB + rs * 2) * 36864;
#pragma unroll 1
            for (int hh = 0; hh < nh; hh++) {
              if (hh == (nh > 3 ? nh - 3 : 0)) mbar_arrive(sreq);
              const int krow = (h0 + hh) * DH;
#pragma unroll 1
              for (int q = 0; q < 5; q++) {
                const uint32_t s = acquire(SLOT);
                if (q == 0 || q == 3) {
                  tma_3d(sbase + s * SLOT, &maps.wo[blk], 0, krow + (q ? 96 : 0), nt * 2, full0 + 8 * s);
                } else {
                  const int kc = q == 4 ? 2 : q - 1;
                  bulk_load(sbase + s * SLOT, src + kc * 12288, 12288, full0 + 8 * s);
                  bulk_load(sbase + s * SLOT + 12288, src + 36864 + kc * 12288, 12288, full0 + 8 * s);
                }
              }
              src += NB * 36864;
            }
          }
        }
      }
    } else if (warp == 1) {
      int pending = -1;
      bool exhausted = O_DEDICATED && (int)blockIdx.x >= N_ATT;
      int task = ticket_task(blockIdx.x);
      for (uint32_t n = 0;; n++) {
        if (lane == 0) {
          mbar_wait(tempty0 + 8 * (n & 3), ((n >> 2) & 1) ^ 1);
          asm volatile("st.shared.b32 [%0], %1;" :: "r"(tbox + 4 * (n & 3)), "r"(task) : "memory");
          mbar_arrive(tfull0 + 8 * (n & 3));
        }
        if (task < 0) break;
        if ((task & 3) == 0) pending = task | 2 | 4;
        mbar_wait(sreq, n & 1);
        task = -2;
        if (!exhausted || pending >= 0) {
          if (task == -2 && pending >= 0) { task = pending; pending = -1; }
          if (task == -2) {
            unsigned int tk = 0;
            if (lane == 0) tk = atomicAdd(&g_ticket, 1u);
            tk = __shfl_sync(0xffffffffu, tk, 0) + gridDim.x;
            if (tk < (unsigned)N_TICKETS) task = ticket_task((int)tk); else exhausted = true;
          }
        }
        if (task == -2) {
          unsigned int cur = 0;
          if (lane == 0) cur = atomicAdd(&g_oticket, 1u);
          cur = __shfl_sync(0xffffffffu, cur, 0);
          if (cur >= (unsigned)N_OTASKS) task = -1;
          else {
            task = o_task((int)cur);
            for (int spin = 0; spin < (1 << 18) && !o_ready(task, lane); spin++) __nanosleep(40);
          }
        }
      }
      unsigned int d = 0;
      if (lane == 0) { __threadfence(); d = atomicAdd(&g_done, 1u); }
      if (__shfl_sync(0xffffffffu, d, 0) == gridDim.x - 1) {
        for (int i = lane; i < 2 * NB * NH; i += 32) g_flag[i] = 0;
        if (lane == 0) { g_ticket = 0; g_oticket = 0; g_oactive = 0; g_done = 0; }
      }
    } else if (warp == 2) {
      uint32_t mu = 0; int mq = 0;
      for (uint32_t n = 0;; n++) {
        int task;
        mbar_wait(tfull0 + 8 * (n & 3), (n >> 2) & 1);
        asm volatile("ld.shared.b32 %0, [%1];" : "=r"(task) : "r"(tbox + 4 * (n & 3)) : "memory");
        __syncwarp();
        if (lane == 0) mbar_arrive(tempty0 + 8 * (n & 3));
        if (task < 0) break;
        if (PFQ > 0 && (task & 3) < 2 && (!PFQ_FIRST || n == 0)) {
          if (n == 0) __nanosleep(PFQ_DELAY);
          const int b = ((task >> 3) & 3) * 2 + ((task >> 2) & 1), h = (task >> 5) & 31, blk = (task >> 10) & 1;
          const size_t off = (size_t)(b * NH + h) * SK * DH * 2 + lane * 128;
#pragma unroll 1
          for (int t = 0; t < PFQ; t++) {
            const uint8_t* p = ((t & 1) ? maps.vp[blk] : maps.kp[blk]) + off + (size_t)(t >> 1) * SLOT;
#pragma unroll
            for (int i = 0; i < 6; i++) asm volatile("prefetch.global.L2 [%0];" :: "l"(p + i * 4096) : "memory");
          }
        }
        if (WO_PF && (n == 1 || n == 2)) {
          const uint8_t* p = maps.wop[n - 1];
          for (int i = blockIdx.x * 32 + lane; i < NH * DH * DM * 2 / 128; i += gridDim.x * 32)
            asm volatile("prefetch.global.L2 [%0];" :: "l"(p + (size_t)i * 128) : "memory");
        }
      }
    } else if (lane == 0) {
      uint32_t na = 0;
      for (uint32_t n = 0;; n++) {
        int task;
        mbar_wait(tfull0 + 8 * (n & 3), (n >> 2) & 1);
        asm volatile("ld.shared.b32 %0, [%1];" : "=r"(task) : "r"(tbox + 4 * (n & 3)) : "memory");
        mbar_arrive(tempty0 + 8 * (n & 3));
        if (task < 0) break;
        if ((task & 3) != 3) {
          mbar_wait(sig, na & 1);
          na++;
          __threadfence();
          const int b = ((task >> 3) & 3) * 2 + ((task >> 2) & 1), h = (task >> 5) & 31, blk = (task >> 10) & 1;
          asm volatile("st.release.gpu.global.u32 [%0], %1;" :: "l"(&g_flag[(blk * NB + b) * NH + h]), "r"(6u) : "memory");
        }
      }
    }
  } else {
    asm volatile("setmaxnreg.inc.sync.aligned.u32 240;");
    const int wg = (warp >> 2) - 1, w = warp & 3, tid = threadIdx.x & 127;
    Cons r; r.base = sbase; r.full0 = full0; r.it = 0; r.lane = lane;
    uint32_t qf[48];
    int dtask = -1;
    STAMP(0, 0);
    for (uint32_t n = 0;; n++) {
      int task;
      if (dtask >= 0 && !mbar_test(tfull0 + 8 * (n & 3), (n >> 2) & 1)) o_complete(dtask, out, wg, w, tid);
      mbar_wait(tfull0 + 8 * (n & 3), (n >> 2) & 1);
      asm volatile("ld.shared.b32 %0, [%1];" : "=r"(task) : "r"(tbox + 4 * (n & 3)) : "memory");
      task = __shfl_sync(0xffffffffu, task, 0);
      if (lane == 0) mbar_arrive(tempty0 + 8 * (n & 3));
      const int type = task & 3;
      if (task < 0) asm volatile("bar.sync 4, 256;" ::: "memory");
      if (task < 0 || type != 3) o_complete(dtask, out, wg, w, tid, task < 0 ? sbase : 0u);
      if (task < 0) break;
      if (type == 3) {
        oproj(r, task, dtask, out, wg, w, tid);
      } else {
        const int bsel = (task >> 2) & 1, pr = (task >> 3) & 3, h = (task >> 5) & 31, blk = (task >> 10) & 1;
        const int b = pr * 2 + bsel;
        bool valid;
        int row8;
        if (type != 2) {
          qproj(r, qf, park, type == 0, wg, tid);
          if (wg == 1 && type == 0) asm volatile("bar.arrive 1, 256;" ::: "memory");
          valid = (wg == 0 || w < 2);
          row8 = wg * 8 + w * 2;
        } else {
          if (wg == 0) {
            asm volatile("bar.sync 1, 256;" ::: "memory");
#pragma unroll
            for (int ks = 0; ks < 12; ks++)
              asm volatile("ld.shared.v4.b32 {%0, %1, %2, %3}, [%4];" : "=r"(qf[4 * ks]), "=r"(qf[4 * ks + 1]), "=r"(qf[4 * ks + 2]), "=r"(qf[4 * ks + 3]) : "r"(park + (ks * 128 + tid) * 16) : "memory");
          }
          valid = (wg == 0 || w >= 2);
          row8 = wg == 0 ? 4 + w * 2 : (w - 2) * 2;
        }
        uint32_t* st = reinterpret_cast<uint32_t*>(g_stash) + (size_t)((blk * NH + h) * NB + b) * 9216 + row8 * 256;
        attention(r, qf, valid, st, sig, wg);
      }
      STAMP(n + 1, task);
    }
  }
}

typedef CUresult (*EncodeFn)(CUtensorMap*, CUtensorMapDataType, cuuint32_t, void*, const cuuint64_t*, const cuuint64_t*, const cuuint32_t*, const cuuint32_t*,
                             CUtensorMapInterleave, CUtensorMapSwizzle, CUtensorMapL2promotion, CUtensorMapFloatOOBfill);

void make_map(EncodeFn fn, CUtensorMap* m, const void* ptr, int rank, const uint64_t* dims, const uint64_t* strides, const uint32_t* box) {
  cuuint32_t es[4] = {1, 1, 1, 1};
  fn(m, CU_TENSOR_MAP_DATA_TYPE_BFLOAT16, rank, const_cast<void*>(ptr), dims, strides, box, es, CU_TENSOR_MAP_INTERLEAVE_NONE,
     CU_TENSOR_MAP_SWIZZLE_128B, CU_TENSOR_MAP_L2_PROMOTION_L2_256B, CU_TENSOR_MAP_FLOAT_OOB_FILL_NONE);
}

}

extern "C" void kernel_launch(void* const* d_in, const int* in_sizes, int n_in, void* d_out, int out_size) {
  static Maps maps;
  static const void* cached[10] = {nullptr};
  static bool init = false;
  static int grid = NCTA;
  bool same = init;
  for (int i = 0; i < 10; i++) same = same && (cached[i] == d_in[i]);
  if (!same) {
    void* fnp = nullptr;
    cudaDriverEntryPointQueryResult qr;
    cudaGetDriverEntryPoint("cuTensorMapEncodeTiled", &fnp, cudaEnableDefault, &qr);
    EncodeFn fn = (EncodeFn)fnp;
    for (int b = 0; b < 2; b++) {
      const void* x = d_in[5 * b + 0]; const void* k = d_in[5 * b + 1]; const void* v = d_in[5 * b + 2];
      const void* wq = d_in[5 * b + 3]; const void* wo = d_in[5 * b + 4];
      maps.wop[b] = (const uint8_t*)wo; maps.kp[b] = (const uint8_t*)k; maps.vp[b] = (const uint8_t*)v;
      { uint64_t d[2] = {DM, NB * SQ}; uint64_t s[1] = {DM * 2}; uint32_t bx[2] = {64, 192}; make_map(fn, &maps.x[b], x, 2, d, s, bx);
        uint32_t b1[2] = {64, 96}; make_map(fn, &maps.x1[b], x, 2, d, s, b1); }
      { uint64_t d[4] = {64, 8, NH * DH / 64, DM / 8}; uint64_t s[3] = {NH * DH * 2, 128, 8 * NH * DH * 2}; uint32_t bx[4] = {64, 8, 3, 8}; make_map(fn, &maps.wq[b], wq, 4, d, s, bx); }
      { uint64_t d[4] = {64, 8, 3, (uint64_t)NB * NH * SK / 8}; uint64_t s[3] = {DH * 2, 128, 8 * DH * 2}; uint32_t bx[4] = {64, 8, 3, 8};
        make_map(fn, &maps.k[b], k, 4, d, s, bx); make_map(fn, &maps.v[b], v, 4, d, s, bx); }
      { uint64_t d[3] = {64, NH * DH, DM / 64}; uint64_t s[2] = {DM * 2, 128}; uint32_t bx[3] = {64, 96, 2}; make_map(fn, &maps.wo[b], wo, 3, d, s, bx); }
    }
    cudaFuncSetAttribute(fused_kernel, cudaFuncAttributeMaxDynamicSharedMemorySize, SMEM_BYTES);
    int dev = 0, sms = NCTA;
    cudaGetDevice(&dev);
    cudaDeviceGetAttribute(&sms, cudaDevAttrMultiProcessorCount, dev);
    grid = sms < NCTA ? sms : NCTA;
    for (int i = 0; i < 10; i++) cached[i] = d_in[i];
    init = true;
  }
  fused_kernel<<<grid, 384, SMEM_BYTES>>>(maps, (__nv_bfloat16*)d_out);
}
```

```cpp
#include <cuda_runtime.h>
#include <cuda_bf16.h>
#include <cuda.h>
#include <stdint.h>

namespace {

constexpr int NB = 8, SQ = 96, DM = 640, NH = 32, SK = 512, DH = 192;
constexpr int SLOT = 24576;
constexpr int NSLOT = 8;
constexpr int SMEM_BYTES = NSLOT * SLOT + SLOT   + 1024   + 256  ;

#define NCTA 132
#define N_ATT 66
#define NPAIR 224
#define FETCH_AHEAD 3
#define KV_INFLIGHT 8
#define WQ_EF 0
#define PDL 1
constexpr int N_TICKETS = NPAIR + 2 * (256 - NPAIR) + (NCTA - N_ATT) / 2;

struct Maps { CUtensorMap x[2], x1[2], wq[2], k[2], v[2], wo[2], wo1[2]; uint32_t otab[66]; };

__device__ uint4 g_stash[2 * NH * NB * 2304];
__device__ float4 g_part[40 * 2 * 24 * 128];
__device__ unsigned int g_tile_cnt[40];
__device__ unsigned int g_flag[2 * NB * NH];
__device__ unsigned int g_ticket, g_done, g_done2;

#define STAMP(i, tk)

__device__ __forceinline__ uint32_t smem_u32(const void* p) { return (uint32_t)__cvta_generic_to_shared(p); }
__device__ __forceinline__ void mbar_init(uint32_t bar, int cnt) { asm volatile("mbarrier.init.shared::cta.b64 [%0], %1;" :: "r"(bar), "r"(cnt) : "memory"); }
__device__ __forceinline__ void mbar_expect_tx(uint32_t bar, uint32_t bytes) { asm volatile("mbarrier.arrive.expect_tx.shared::cta.b64 _, [%0], %1;" :: "r"(bar), "r"(bytes) : "memory"); }
__device__ __forceinline__ void mbar_arrive(uint32_t bar) { asm volatile("mbarrier.arrive.shared::cta.b64 _, [%0];" :: "r"(bar) : "memory"); }
__device__ __forceinline__ void mbar_wait(uint32_t bar, uint32_t parity) {
  asm volatile("{\n.reg .pred p;\nWAIT_%=:\nmbarrier.try_wait.parity.shared::cta.b64 p, [%0], %1;\n@p bra DONE_%=;\nbra WAIT_%=;\nDONE_%=:\n}" :: "r"(bar), "r"(parity) : "memory");
}
__device__ __forceinline__ void tma_2d(uint32_t dst, const CUtensorMap* m, int c0, int c1, uint32_t bar) {
  asm volatile("cp.async.bulk.tensor.2d.shared::cluster.global.mbarrier::complete_tx::bytes [%0], [%1, {%3, %4}], [%2];"
               :: "r"(dst), "l"(m), "r"(bar), "r"(c0), "r"(c1) : "memory");
}
__device__ __forceinline__ void tma_3d(uint32_t dst, const CUtensorMap* m, int c0, int c1, int c2, uint32_t bar) {
  asm volatile("cp.async.bulk.tensor.3d.shared::cluster.global.mbarrier::complete_tx::bytes [%0], [%1, {%3, %4, %5}], [%2];"
               :: "r"(dst), "l"(m), "r"(bar), "r"(c0), "r"(c1), "r"(c2) : "memory");
}
__device__ __forceinline__ void tma_4d(uint32_t dst, const CUtensorMap* m, int c2, int c3, uint32_t bar) {
  asm volatile("cp.async.bulk.tensor.4d.shared::cluster.global.mbarrier::complete_tx::bytes [%0], [%1, {%3, %3, %4, %5}], [%2];"
               :: "r"(dst), "l"(m), "r"(bar), "r"(0), "r"(c2), "r"(c3) : "memory");
}
__device__ __forceinline__ void tma_4d_hint(uint32_t dst, const CUtensorMap* m, int c2, int c3, uint32_t bar, uint64_t pol) {
  asm volatile("cp.async.bulk.tensor.4d.shared::cluster.global.mbarrier::complete_tx::bytes.L2::cache_hint [%0], [%1, {%3, %3, %4, %5}], [%2], %6;"
               :: "r"(dst), "l"(m), "r"(bar), "r"(0), "r"(c2), "r"(c3), "l"(pol) : "memory");
}
__device__ __forceinline__ void bulk_load(uint32_t dst, const void* src, uint32_t bytes, uint32_t bar) {
  asm volatile("cp.async.bulk.shared::cluster.global.mbarrier::complete_tx::bytes [%0], [%1], %2, [%3];" :: "r"(dst), "l"(src), "r"(bytes), "r"(bar) : "memory");
}
__device__ __forceinline__ void wg_fence() { asm volatile("wgmma.fence.sync.aligned;" ::: "memory"); }
__device__ __forceinline__ void wg_commit() { asm volatile("wgmma.commit_group.sync.aligned;" ::: "memory"); }
template <int N> __device__ __forceinline__ void wg_wait() { asm volatile("wgmma.wait_group.sync.aligned %0;" :: "n"(N) : "memory"); }
template <int N> __device__ __forceinline__ void touch(float (&d)[N]) {
#pragma unroll
  for (int i = 0; i < N; i++) asm volatile("" : "+f"(d[i]) :: "memory");
}
template <int N> __device__ __forceinline__ void touch_u(uint32_t (&d)[N]) {
#pragma unroll
  for (int i = 0; i < N; i++) asm volatile("" : "+r"(d[i]) :: "memory");
}
__device__ __forceinline__ float ex2(float x) { float y; asm("ex2.approx.ftz.f32 %0, %1;" : "=f"(y) : "f"(x)); return y; }
__device__ __forceinline__ uint32_t pack_bf16(float lo, float hi) { uint32_t r; asm("cvt.rn.bf16x2.f32 %0, %1, %2;" : "=r"(r) : "f"(hi), "f"(lo)); return r; }

constexpr uint64_t DESC_SW128 = (uint64_t)1 << 62;
__device__ __forceinline__ uint64_t desc_kmajor_sw128(uint32_t addr) {
  return DESC_SW128 | ((uint64_t)(1024 >> 4) << 32) | ((uint64_t)1 << 16) | (uint64_t)((addr & 0x3FFFF) >> 4);
}
__device__ __forceinline__ uint64_t desc_k_il(uint32_t addr) {
  return DESC_SW128 | ((uint64_t)(3072 >> 4) << 32) | ((uint64_t)1 << 16) | (uint64_t)((addr & 0x3FFFF) >> 4);
}
__device__ __forceinline__ uint64_t desc_mn_il(uint32_t addr) {
  return DESC_SW128 | ((uint64_t)(3072 >> 4) << 32) | ((uint64_t)(1024 >> 4) << 16) | (uint64_t)((addr & 0x3FFFF) >> 4);
}
template <int LBO> __device__ __forceinline__ uint64_t desc_mnmajor_sw128(uint32_t addr) {
  return DESC_SW128 | ((uint64_t)(1024 >> 4) << 32) | ((uint64_t)(LBO >> 4) << 16) | (uint64_t)((addr & 0x3FFFF) >> 4);
}
__device__ __forceinline__ uint64_t desc_kmajor_nosw(uint32_t addr) {
  return ((uint64_t)(1024 >> 4) << 32) | ((uint64_t)(128 >> 4) << 16) | (uint64_t)((addr & 0x3FFFF) >> 4);
}

__device__ __forceinline__ void wgmma_rs_n64_t0(float (&d)[32], uint32_t a0, uint32_t a1, uint32_t a2, uint32_t a3, uint64_t descB, int scaleD) {
  asm volatile("{\n.reg .pred p;\nsetp.ne.b32 p, %37, 0;\n"
    "wgmma.mma_async.sync.aligned.m64n64k16.f32.bf16.bf16 "
    "{%0, %1, %2, %3, %4, %5, %6, %7, %8, %9, %10, %11, %12, %13, %14, %15, %16, %17, %18, %19, %20, %21, %22, %23, %24, %25, %26, %27, %28, %29, %30, %31}, "
    "{%32, %33, %34, %35}, %36, p, 1, 1, 0;\n}\n"
    : "+f"(d[0]), "+f"(d[1]), "+f"(d[2]), "+f"(d[3]), "+f"(d[4]), "+f"(d[5]), "+f"(d[6]), "+f"(d[7]), "+f"(d[8]), "+f"(d[9]), "+f"(d[10]), "+f"(d[11]), "+f"(d[12]), "+f"(d[13]), "+f"(d[14]), "+f"(d[15]), "+f"(d[16]), "+f"(d[17]), "+f"(d[18]), "+f"(d[19]), "+f"(d[20]), "+f"(d[21]), "+f"(d[22]), "+f"(d[23]), "+f"(d[24]), "+f"(d[25]), "+f"(d[26]), "+f"(d[27]), "+f"(d[28]), "+f"(d[29]), "+f"(d[30]), "+f"(d[31])
    : "r"(a0), "r"(a1), "r"(a2), "r"(a3), "l"(descB), "r"(scaleD));
}
__device__ __forceinline__ void wgmma_rs_n192_t1(float (&d)[96], uint32_t a0, uint32_t a1, uint32_t a2, uint32_t a3, uint64_t descB, int scaleD) {
  asm volatile("{\n.reg .pred p;\nsetp.ne.b32 p, %101, 0;\n"
    "wgmma.mma_async.sync.aligned.m64n192k16.f32.bf16.bf16 "
    "{%0, %1, %2, %3, %4, %5, %6, %7, %8, %9, %10, %11, %12, %13, %14, %15, %16, %17, %18, %19, %20, %21, %22, %23, %24, %25, %26, %27, %28, %29, %30, %31, %32, %33, %34, %35, %36, %37, %38, %39, %40, %41, %42, %43, %44, %45, %46, %47, %48, %49, %50, %51, %52, %53, %54, %55, %56, %57, %58, %59, %60, %61, %62, %63, %64, %65, %66, %67, %68, %69, %70, %71, %72, %73, %74, %75, %76, %77, %78, %79, %80, %81, %82, %83, %84, %85, %86, %87, %88, %89, %90, %91, %92, %93, %94, %95}, "
    "{%96, %97, %98, %99}, %100, p, 1, 1, 1;\n}\n"
    : "+f"(d[0]), "+f"(d[1]), "+f"(d[2]), "+f"(d[3]), "+f"(d[4]), "+f"(d[5]), "+f"(d[6]), "+f"(d[7]), "+f"(d[8]), "+f"(d[9]), "+f"(d[10]), "+f"(d[11]), "+f"(d[12]), "+f"(d[13]), "+f"(d[14]), "+f"(d[15]), "+f"(d[16]), "+f"(d[17]), "+f"(d[18]), "+f"(d[19]), "+f"(d[20]), "+f"(d[21]), "+f"(d[22]), "+f"(d[23]), "+f"(d[24]), "+f"(d[25]), "+f"(d[26]), "+f"(d[27]), "+f"(d[28]), "+f"(d[29]), "+f"(d[30]), "+f"(d[31]), "+f"(d[32]), "+f"(d[33]), "+f"(d[34]), "+f"(d[35]), "+f"(d[36]), "+f"(d[37]), "+f"(d[38]), "+f"(d[39]), "+f"(d[40]), "+f"(d[41]), "+f"(d[42]), "+f"(d[43]), "+f"(d[44]), "+f"(d[45]), "+f"(d[46]), "+f"(d[47]), "+f"(d[48]), "+f"(d[49]), "+f"(d[50]), "+f"(d[51]), "+f"(d[52]), "+f"(d[53]), "+f"(d[54]), "+f"(d[55]), "+f"(d[56]), "+f"(d[57]), "+f"(d[58]), "+f"(d[59]), "+f"(d[60]), "+f"(d[61]), "+f"(d[62]), "+f"(d[63]), "+f"(d[64]), "+f"(d[65]), "+f"(d[66]), "+f"(d[67]), "+f"(d[68]), "+f"(d[69]), "+f"(d[70]), "+f"(d[71]), "+f"(d[72]), "+f"(d[73]), "+f"(d[74]), "+f"(d[75]), "+f"(d[76]), "+f"(d[77]), "+f"(d[78]), "+f"(d[79]), "+f"(d[80]), "+f"(d[81]), "+f"(d[82]), "+f"(d[83]), "+f"(d[84]), "+f"(d[85]), "+f"(d[86]), "+f"(d[87]), "+f"(d[88]), "+f"(d[89]), "+f"(d[90]), "+f"(d[91]), "+f"(d[92]), "+f"(d[93]), "+f"(d[94]), "+f"(d[95])
    : "r"(a0), "r"(a1), "r"(a2), "r"(a3), "l"(descB), "r"(scaleD));
}
__device__ __forceinline__ void wgmma_ss_n192_t1(float (&d)[96], uint64_t descA, uint64_t descB, int scaleD) {
  asm volatile("{\n.reg .pred p;\nsetp.ne.b32 p, %98, 0;\n"
    "wgmma.mma_async.sync.aligned.m64n192k16.f32.bf16.bf16 "
    "{%0, %1, %2, %3, %4, %5, %6, %7, %8, %9, %10, %11, %12, %13, %14, %15, %16, %17, %18, %19, %20, %21, %22, %23, %24, %25, %26, %27, %28, %29, %30, %31, %32, %33, %34, %35, %36, %37, %38, %39, %40, %41, %42, %43, %44, %45, %46, %47, %48, %49, %50, %51, %52, %53, %54, %55, %56, %57, %58, %59, %60, %61, %62, %63, %64, %65, %66, %67, %68, %69, %70, %71, %72, %73, %74, %75, %76, %77, %78, %79, %80, %81, %82, %83, %84, %85, %86, %87, %88, %89, %90, %91, %92, %93, %94, %95}, "
    "%96, %97, p, 1, 1, 0, 1;\n}\n"
    : "+f"(d[0]), "+f"(d[1]), "+f"(d[2]), "+f"(d[3]), "+f"(d[4]), "+f"(d[5]), "+f"(d[6]), "+f"(d[7]), "+f"(d[8]), "+f"(d[9]), "+f"(d[10]), "+f"(d[11]), "+f"(d[12]), "+f"(d[13]), "+f"(d[14]), "+f"(d[15]), "+f"(d[16]), "+f"(d[17]), "+f"(d[18]), "+f"(d[19]), "+f"(d[20]), "+f"(d[21]), "+f"(d[22]), "+f"(d[23]), "+f"(d[24]), "+f"(d[25]), "+f"(d[26]), "+f"(d[27]), "+f"(d[28]), "+f"(d[29]), "+f"(d[30]), "+f"(d[31]), "+f"(d[32]), "+f"(d[33]), "+f"(d[34]), "+f"(d[35]), "+f"(d[36]), "+f"(d[37]), "+f"(d[38]), "+f"(d[39]), "+f"(d[40]), "+f"(d[41]), "+f"(d[42]), "+f"(d[43]), "+f"(d[44]), "+f"(d[45]), "+f"(d[46]), "+f"(d[47]), "+f"(d[48]), "+f"(d[49]), "+f"(d[50]), "+f"(d[51]), "+f"(d[52]), "+f"(d[53]), "+f"(d[54]), "+f"(d[55]), "+f"(d[56]), "+f"(d[57]), "+f"(d[58]), "+f"(d[59]), "+f"(d[60]), "+f"(d[61]), "+f"(d[62]), "+f"(d[63]), "+f"(d[64]), "+f"(d[65]), "+f"(d[66]), "+f"(d[67]), "+f"(d[68]), "+f"(d[69]), "+f"(d[70]), "+f"(d[71]), "+f"(d[72]), "+f"(d[73]), "+f"(d[74]), "+f"(d[75]), "+f"(d[76]), "+f"(d[77]), "+f"(d[78]), "+f"(d[79]), "+f"(d[80]), "+f"(d[81]), "+f"(d[82]), "+f"(d[83]), "+f"(d[84]), "+f"(d[85]), "+f"(d[86]), "+f"(d[87]), "+f"(d[88]), "+f"(d[89]), "+f"(d[90]), "+f"(d[91]), "+f"(d[92]), "+f"(d[93]), "+f"(d[94]), "+f"(d[95])
    : "l"(descA), "l"(descB), "r"(scaleD));
}
__device__ __forceinline__ void wgmma_ss_n64_t1(float (&d)[32], uint64_t descA, uint64_t descB, int scaleD) {
  asm volatile("{\n.reg .pred p;\nsetp.ne.b32 p, %34, 0;\n"
    "wgmma.mma_async.sync.aligned.m64n64k16.f32.bf16.bf16 "
    "{%0, %1, %2, %3, %4, %5, %6, %7, %8, %9, %10, %11, %12, %13, %14, %15, %16, %17, %18, %19, %20, %21, %22, %23, %24, %25, %26, %27, %28, %29, %30, %31}, "
    "%32, %33, p, 1, 1, 0, 1;\n}\n"
    : "+f"(d[0]), "+f"(d[1]), "+f"(d[2]), "+f"(d[3]), "+f"(d[4]), "+f"(d[5]), "+f"(d[6]), "+f"(d[7]), "+f"(d[8]), "+f"(d[9]), "+f"(d[10]), "+f"(d[11]), "+f"(d[12]), "+f"(d[13]), "+f"(d[14]), "+f"(d[15]), "+f"(d[16]), "+f"(d[17]), "+f"(d[18]), "+f"(d[19]), "+f"(d[20]), "+f"(d[21]), "+f"(d[22]), "+f"(d[23]), "+f"(d[24]), "+f"(d[25]), "+f"(d[26]), "+f"(d[27]), "+f"(d[28]), "+f"(d[29]), "+f"(d[30]), "+f"(d[31])
    : "l"(descA), "l"(descB), "r"(scaleD));
}
__device__ __forceinline__ void wgmma_ss_n32_t1(float (&d)[16], uint64_t descA, uint64_t descB, int scaleD) {
  asm volatile("{\n.reg .pred p;\nsetp.ne.b32 p, %18, 0;\n"
    "wgmma.mma_async.sync.aligned.m64n32k16.f32.bf16.bf16 "
    "{%0, %1, %2, %3, %4, %5, %6, %7, %8, %9, %10, %11, %12, %13, %14, %15}, "
    "%16, %17, p, 1, 1, 0, 1;\n}\n"
    : "+f"(d[0]), "+f"(d[1]), "+f"(d[2]), "+f"(d[3]), "+f"(d[4]), "+f"(d[5]), "+f"(d[6]), "+f"(d[7]), "+f"(d[8]), "+f"(d[9]), "+f"(d[10]), "+f"(d[11]), "+f"(d[12]), "+f"(d[13]), "+f"(d[14]), "+f"(d[15])
    : "l"(descA), "l"(descB), "r"(scaleD));
}
__device__ __forceinline__ void wgmma_st_n192_t0(float (&d)[96], uint64_t descA, uint64_t descB, int scaleD) {
  asm volatile("{\n.reg .pred p;\nsetp.ne.b32 p, %98, 0;\n"
    "wgmma.mma_async.sync.aligned.m64n192k16.f32.bf16.bf16 "
    "{%0, %1, %2, %3, %4, %5, %6, %7, %8, %9, %10, %11, %12, %13, %14, %15, %16, %17, %18, %19, %20, %21, %22, %23, %24, %25, %26, %27, %28, %29, %30, %31, %32, %33, %34, %35, %36, %37, %38, %39, %40, %41, %42, %43, %44, %45, %46, %47, %48, %49, %50, %51, %52, %53, %54, %55, %56, %57, %58, %59, %60, %61, %62, %63, %64, %65, %66, %67, %68, %69, %70, %71, %72, %73, %74, %75, %76, %77, %78, %79, %80, %81, %82, %83, %84, %85, %86, %87, %88, %89, %90, %91, %92, %93, %94, %95}, "
    "%96, %97, p, 1, 1, 1, 0;\n}\n"
    : "+f"(d[0]), "+f"(d[1]), "+f"(d[2]), "+f"(d[3]), "+f"(d[4]), "+f"(d[5]), "+f"(d[6]), "+f"(d[7]), "+f"(d[8]), "+f"(d[9]), "+f"(d[10]), "+f"(d[11]), "+f"(d[12]), "+f"(d[13]), "+f"(d[14]), "+f"(d[15]), "+f"(d[16]), "+f"(d[17]), "+f"(d[18]), "+f"(d[19]), "+f"(d[20]), "+f"(d[21]), "+f"(d[22]), "+f"(d[23]), "+f"(d[24]), "+f"(d[25]), "+f"(d[26]), "+f"(d[27]), "+f"(d[28]), "+f"(d[29]), "+f"(d[30]), "+f"(d[31]), "+f"(d[32]), "+f"(d[33]), "+f"(d[34]), "+f"(d[35]), "+f"(d[36]), "+f"(d[37]), "+f"(d[38]), "+f"(d[39]), "+f"(d[40]), "+f"(d[41]), "+f"(d[42]), "+f"(d[43]), "+f"(d[44]), "+f"(d[45]), "+f"(d[46]), "+f"(d[47]), "+f"(d[48]), "+f"(d[49]), "+f"(d[50]), "+f"(d[51]), "+f"(d[52]), "+f"(d[53]), "+f"(d[54]), "+f"(d[55]), "+f"(d[56]), "+f"(d[57]), "+f"(d[58]), "+f"(d[59]), "+f"(d[60]), "+f"(d[61]), "+f"(d[62]), "+f"(d[63]), "+f"(d[64]), "+f"(d[65]), "+f"(d[66]), "+f"(d[67]), "+f"(d[68]), "+f"(d[69]), "+f"(d[70]), "+f"(d[71]), "+f"(d[72]), "+f"(d[73]), "+f"(d[74]), "+f"(d[75]), "+f"(d[76]), "+f"(d[77]), "+f"(d[78]), "+f"(d[79]), "+f"(d[80]), "+f"(d[81]), "+f"(d[82]), "+f"(d[83]), "+f"(d[84]), "+f"(d[85]), "+f"(d[86]), "+f"(d[87]), "+f"(d[88]), "+f"(d[89]), "+f"(d[90]), "+f"(d[91]), "+f"(d[92]), "+f"(d[93]), "+f"(d[94]), "+f"(d[95])
    : "l"(descA), "l"(descB), "r"(scaleD));
}

__device__ __forceinline__ unsigned int ld_acquire(const unsigned int* p) { unsigned int v; asm volatile("ld.acquire.gpu.global.u32 %0, [%1];" : "=r"(v) : "l"(p) : "memory"); return v; }

struct Cons {
  uint32_t base, full0;
  uint32_t it;
  int lane;
  __device__ __forceinline__ uint32_t wait(uint32_t slot, uint32_t u) const { mbar_wait(full0 + slot * 8, (u >> 3) & 1); return base + slot * SLOT; }
  __device__ __forceinline__ uint32_t wait(uint32_t u) const { return wait(u & 7, u); }
  __device__ __forceinline__ void release(uint32_t slot) const { if (lane == 0) mbar_arrive(full0 + 64 + (slot & 7) * 8); }
};

__device__ __forceinline__ int ticket_task(int ticket) {
  int u = ticket, f = 0;
  if (ticket >= N_ATT) {
    if (ticket < NCTA) { const int s = ticket - N_ATT; u = N_ATT + (s >> 1); f = 1 | ((s & 1) << 2); }
    else {
      u = ticket - (NCTA - N_ATT) / 2;
      if (u >= NPAIR) { const int s = u - NPAIR; u = NPAIR + (s >> 1); f = 1 | ((s & 1) << 2); }
    }
  }
  const int hh = u & 7, pr = (u >> 3) & 3, g = (u >> 5) & 3, blk = u >> 7;
  return f | (pr << 3) | ((g * 8 + hh) << 5) | (blk << 10);
}

__device__ __forceinline__ void qproj(Cons& r, uint32_t (&qf)[48], uint32_t park, bool pair, int wg, int tid) {
  float acc[96];
  float acx[32];
  float acy[16];
  for (int c = 0; c < 10; c++) {
    const uint32_t sx = r.it;
    const uint32_t xa = r.wait(sx), wa = r.wait(sx + 1);
    const uint64_t da = desc_kmajor_sw128(xa + wg * 8192), d2 = desc_kmajor_sw128(xa + 2 * 8192);
    const uint64_t db = desc_mn_il(wa), dbx = desc_mn_il(wa + wg * 1024), dby = desc_mn_il(wa + 2048 + wg * 64);
    if (pair) {
      wg_fence();
#pragma unroll
      for (int ks = 0; ks < 4; ks++) {
        const int sc = (c > 0 || ks > 0) ? 1 : 0;
        wgmma_ss_n192_t1(acc, da + ks * 2, db + ks * 384, sc);
        wgmma_ss_n64_t1(acx, d2 + ks * 2, dbx + ks * 384, sc);
        wgmma_ss_n32_t1(acy, d2 + ks * 2, dby + ks * 384, sc);
      }
      wg_commit();
    } else {
      wg_fence();
#pragma unroll
      for (int ks = 0; ks < 4; ks++)
        wgmma_ss_n192_t1(acc, da + ks * 2, db + ks * 384, (c > 0 || ks > 0) ? 1 : 0);
      wg_commit();
    }
    if (c > 0) { wg_wait<1>(); r.release((sx + 6) & 7); r.release((sx + 7) & 7); }
    r.it += 2;
  }
  wg_wait<0>();
  touch(acc); touch(acx); touch(acy);
  r.release((r.it + 6) & 7); r.release((r.it + 7) & 7);
  if (pair) {
#pragma unroll
    for (int ks = 0; ks < 4; ks++) {
      uint32_t a0 = pack_bf16(acx[8 * ks + 0], acx[8 * ks + 1]), a1 = pack_bf16(acx[8 * ks + 2], acx[8 * ks + 3]);
      uint32_t a2 = pack_bf16(acx[8 * ks + 4], acx[8 * ks + 5]), a3 = pack_bf16(acx[8 * ks + 6], acx[8 * ks + 7]);
      asm volatile("st.shared.v4.b32 [%0], {%1, %2, %3, %4};" :: "r"(park + ((wg * 4 + ks) * 128 + tid) * 16), "r"(a0), "r"(a1), "r"(a2), "r"(a3) : "memory");
    }
#pragma unroll
    for (int ks = 0; ks < 2; ks++) {
      uint32_t a0 = pack_bf16(acy[8 * ks + 0], acy[8 * ks + 1]), a1 = pack_bf16(acy[8 * ks + 2], acy[8 * ks + 3]);
      uint32_t a2 = pack_bf16(acy[8 * ks + 4], acy[8 * ks + 5]), a3 = pack_bf16(acy[8 * ks + 6], acy[8 * ks + 7]);
      asm volatile("st.shared.v4.b32 [%0], {%1, %2, %3, %4};" :: "r"(park + ((8 + wg * 2 + ks) * 128 + tid) * 16), "r"(a0), "r"(a1), "r"(a2), "r"(a3) : "memory");
    }
  }
#pragma unroll
  for (int i = 0; i < 48; i++) qf[i] = pack_bf16(acc[2 * i], acc[2 * i + 1]);
}

__device__ __forceinline__ void sched_sync(int wg) { asm volatile("bar.sync %0, 256;" :: "r"(2 + wg) : "memory"); }
__device__ __forceinline__ void sched_arrive(int wg) { asm volatile("bar.arrive %0, 256;" :: "r"(3 - wg) : "memory"); }

__device__ __forceinline__ void issue_qk(float (&s)[32], const uint32_t (&qf)[48], uint64_t dk) {
#pragma unroll
  for (int ks = 0; ks < 12; ks++)
    wgmma_rs_n64_t0(s, qf[4 * ks], qf[4 * ks + 1], qf[4 * ks + 2], qf[4 * ks + 3], dk + ((ks >> 2) * 64 + (ks & 3) * 2), ks > 0);
  wg_commit();
}
__device__ __forceinline__ void attention(Cons& r, const uint32_t (&qf)[48], bool valid, uint32_t* dst, uint32_t sig, int wg) {
  constexpr float CS = 0.07216878364870322f * 1.4426950408889634f;
  const int lane = r.lane;
  float o[96];
  float s[32];
  uint32_t pa[8], pb[8];
  float m0 = -INFINITY, m1 = -INFINITY, l0 = 0.f, l1 = 0.f, al0 = 1.f, al1 = 1.f;
  bool resc = false;
#pragma unroll
  for (int i = 0; i < 8; i++) { pa[i] = 0; pb[i] = 0; }

  auto row_max = [&]() {
    float x0 = fmaxf(s[0], s[1]), x1 = fmaxf(s[2], s[3]), y0 = fmaxf(s[4], s[5]), y1 = fmaxf(s[6], s[7]);
#pragma unroll
    for (int i = 2; i < 8; i += 2) {
      x0 = fmaxf(x0, fmaxf(s[4 * i], s[4 * i + 1])); x1 = fmaxf(x1, fmaxf(s[4 * i + 2], s[4 * i + 3]));
      y0 = fmaxf(y0, fmaxf(s[4 * i + 4], s[4 * i + 5])); y1 = fmaxf(y1, fmaxf(s[4 * i + 6], s[4 * i + 7]));
    }
    x0 = fmaxf(x0, y0); x1 = fmaxf(x1, y1);
    x0 = fmaxf(x0, __shfl_xor_sync(0xffffffffu, x0, 1)); x1 = fmaxf(x1, __shfl_xor_sync(0xffffffffu, x1, 1));
    x0 = fmaxf(x0, __shfl_xor_sync(0xffffffffu, x0, 2)); x1 = fmaxf(x1, __shfl_xor_sync(0xffffffffu, x1, 2));
    resc = __any_sync(0xffffffffu, (x0 - m0) * CS > 8.0f || (x1 - m1) * CS > 8.0f);
    if (resc) {
      const float n0 = fmaxf(m0, x0), n1 = fmaxf(m1, x1);
      al0 = ex2((m0 - n0) * CS); al1 = ex2((m1 - n1) * CS);
      m0 = n0; m1 = n1;
      l0 *= al0; l1 *= al1;
    }
  };
  auto exps = [&](uint32_t (&p)[8], int h) {
    const float c0 = m0 * CS, c1 = m1 * CS;
    float t0 = 0.f, t1 = 0.f;
#pragma unroll
    for (int i = 0; i < 4; i++) {
      const int k = 16 * h + 4 * i;
      const float e0 = ex2(fmaf(s[k], CS, -c0)), e1 = ex2(fmaf(s[k + 1], CS, -c0));
      const float e2 = ex2(fmaf(s[k + 2], CS, -c1)), e3 = ex2(fmaf(s[k + 3], CS, -c1));
      t0 += e0 + e1; t1 += e2 + e3;
      p[2 * i] = pack_bf16(e0, e1); p[2 * i + 1] = pack_bf16(e2, e3);
    }
    l0 += t0; l1 += t1;
  };
  auto pv_a = [&](uint64_t dv, int first) {
    wgmma_rs_n192_t1(o, pa[0], pa[1], pa[2], pa[3], dv, first ? 0 : 1);
    wgmma_rs_n192_t1(o, pa[4], pa[5], pa[6], pa[7], dv + 384, 1);
    wg_commit();
  };
  auto pv_b = [&](uint64_t dv) {
    wgmma_rs_n192_t1(o, pb[0], pb[1], pb[2], pb[3], dv + 768, 1);
    wgmma_rs_n192_t1(o, pb[4], pb[5], pb[6], pb[7], dv + 1152, 1);
    wg_commit();
  };

  if (wg == 1) sched_arrive(1);
  {
    const uint32_t sk = r.it & 7;
    const uint64_t dk = desc_k_il(r.wait(sk, r.it));
    sched_sync(wg);
    wg_fence();
    issue_qk(s, qf, dk);
    sched_arrive(wg);
    wg_wait<0>();
    touch(s);
    r.release(sk);
    if (valid) { row_max(); exps(pa, 0); exps(pb, 1); }
  }
  for (int j = 0; j < 7; j++) {
    const uint32_t u = r.it;
    const uint32_t sv = (u + 1) & 7, sk = (u + 2) & 7;
    const uint64_t dk = desc_k_il(r.wait(sk, u + 2));
    const uint64_t dv = desc_mn_il(r.wait(sv, u + 1));
    sched_sync(wg);
    wg_fence();
    issue_qk(s, qf, dk);
    pv_a(dv, j == 0);
    pv_b(dv);
    sched_arrive(wg);
    wg_wait<2>();
    touch(s);
    r.release(sk);
    if (valid) row_max();
    wg_wait<1>();
    touch_u(pa);
    if (valid) exps(pa, 0);
    touch_u(pa);
    wg_wait<0>();
    touch(o); touch_u(pb);
    r.release(sv);
    if (valid) exps(pb, 1);
    if (resc) {
#pragma unroll
      for (int i = 0; i < 24; i++) { o[4 * i] *= al0; o[4 * i + 1] *= al0; o[4 * i + 2] *= al1; o[4 * i + 3] *= al1; }
    }
    touch_u(pb);
    r.it += 2;
  }
  {
    const uint32_t sv = (r.it + 1) & 7;
    const uint64_t dv = desc_mn_il(r.wait(sv, r.it + 1));
    sched_sync(wg);
    wg_fence();
    pv_a(dv, 0);
    pv_b(dv);
    if (wg == 0) sched_arrive(0);
    wg_wait<0>();
    touch(o); touch_u(pa); touch_u(pb);
    r.release(sv);
    r.it += 2;
  }
  if (valid) {
    l0 += __shfl_xor_sync(0xffffffffu, l0, 1); l1 += __shfl_xor_sync(0xffffffffu, l1, 1);
    l0 += __shfl_xor_sync(0xffffffffu, l0, 2); l1 += __shfl_xor_sync(0xffffffffu, l1, 2);
    const float i0 = 1.0f / l0, i1 = 1.0f / l1;
#pragma unroll
    for (int kc = 0; kc < 24; kc++) {
      dst[(kc >> 3) * 3072 + (kc & 7) * 32 + lane] = pack_bf16(o[4 * kc] * i0, o[4 * kc + 1] * i0);
      dst[(kc >> 3) * 3072 + 256 + (kc & 7) * 32 + lane] = pack_bf16(o[4 * kc + 2] * i1, o[4 * kc + 3] * i1);
    }
    __syncwarp();
    if (lane == 0) mbar_arrive(sig);
  }
}

__global__ void __launch_bounds__(384, 1) attn_kernel(const __grid_constant__ Maps maps) {
  extern __shared__ uint8_t smem_raw[];
  const uint32_t sbase = (smem_u32(smem_raw) + 1023u) & ~1023u;
  const uint32_t park = sbase + NSLOT * SLOT;
  const uint32_t bars = park + SLOT;
  const uint32_t full0 = bars, empty0 = bars + 64;
  const uint32_t tfull0 = bars + 128, tempty0 = bars + 160, sig0 = bars + 192, tbox = bars + 224, sreq = bars + 240;
  const int warp = __shfl_sync(0xffffffffu, threadIdx.x >> 5, 0), lane = threadIdx.x & 31;
  if (threadIdx.x == 0) {
    for (int i = 0; i < NSLOT; i++) { mbar_init(full0 + 8 * i, 1); mbar_init(empty0 + 8 * i, 8); }
    for (int i = 0; i < 4; i++) { mbar_init(tfull0 + 8 * i, 1); mbar_init(tempty0 + 8 * i, 10); mbar_init(sig0 + 8 * i, 6); }
    mbar_init(sreq, 1);
    asm volatile("fence.mbarrier_init.release.cluster;" ::: "memory");
  }
  __syncthreads();
  asm volatile("griddepcontrol.launch_dependents;");

  if (warp < 4) {
    asm volatile("setmaxnreg.dec.sync.aligned.u32 24;");
    if (warp == 0 && lane == 0) {
      uint64_t pol; asm volatile("createpolicy.fractional.L2::evict_first.b64 %0, 1.0;" : "=l"(pol));
      uint32_t u = 0;
      auto acquire = [&](uint32_t bytes) -> uint32_t {
        const uint32_t s = u & 7;
        mbar_wait(empty0 + 8 * s, ((u >> 3) & 1) ^ 1);
        mbar_expect_tx(full0 + 8 * s, bytes);
        u++;
        return s;
      };
      for (uint32_t n = 0;; n++) {
        int task;
        mbar_wait(tfull0 + 8 * (n & 3), (n >> 2) & 1);
        asm volatile("ld.shared.b32 %0, [%1];" : "=r"(task) : "r"(tbox + 4 * (n & 3)) : "memory");
        mbar_arrive(tempty0 + 8 * (n & 3));
        if (task < 0) break;
        const int type = task & 3, bsel = (task >> 2) & 1, pr = (task >> 3) & 3, h = (task >> 5) & 31, blk = (task >> 10) & 1;
        if (type != 2) {
          const CUtensorMap* mx = type ? &maps.x1[blk] : &maps.x[blk];
#pragma unroll 1
          for (int c = 0; c < 10; c++) {
            uint32_t s = acquire(type ? SLOT / 2 : SLOT);
            tma_2d(sbase + s * SLOT, mx, c * 64, pr * 192 + bsel * 96, full0 + 8 * s);
            s = acquire(SLOT);
            if (WQ_EF) tma_4d_hint(sbase + s * SLOT, &maps.wq[blk], h * 3, c * 8, full0 + 8 * s, pol);
            else tma_4d(sbase + s * SLOT, &maps.wq[blk], h * 3, c * 8, full0 + 8 * s);
          }
        }
        int rg = (((pr * 2 + bsel) * NH + h) * SK) >> 3;
#pragma unroll 1
        for (int j = 0; j < 8; j++) {
          if (j == 8 - FETCH_AHEAD) mbar_arrive(sreq);
          if (KV_INFLIGHT < 8 && u >= KV_INFLIGHT) mbar_wait(full0 + 8 * ((u - KV_INFLIGHT) & 7), ((u - KV_INFLIGHT) >> 3) & 1);
          uint32_t s = acquire(SLOT);
          tma_4d_hint(sbase + s * SLOT, &maps.k[blk], 0, rg, full0 + 8 * s, pol);
          if (KV_INFLIGHT < 8 && u >= KV_INFLIGHT) mbar_wait(full0 + 8 * ((u - KV_INFLIGHT) & 7), ((u - KV_INFLIGHT) >> 3) & 1);
          s = acquire(SLOT);
          tma_4d_hint(sbase + s * SLOT, &maps.v[blk], 0, rg, full0 + 8 * s, pol);
          rg += 8;
        }
      }
    } else if (warp == 1 && lane == 0) {
      int task = ticket_task(blockIdx.x);
      for (uint32_t n = 0;; n++) {
        mbar_wait(tempty0 + 8 * (n & 3), ((n >> 2) & 1) ^ 1);
        asm volatile("st.shared.b32 [%0], %1;" :: "r"(tbox + 4 * (n & 3)), "r"(task) : "memory");
        mbar_arrive(tfull0 + 8 * (n & 3));
        if (task < 0) break;
        if ((task & 3) == 0) {
          task |= 2 | 4;
        } else {
          mbar_wait(sreq, n & 1);
          const unsigned int tk = atomicAdd(&g_ticket, 1u) + gridDim.x;
          task = tk < (unsigned)N_TICKETS ? ticket_task((int)tk) : -1;
          continue;
        }
        mbar_wait(sreq, n & 1);
      }
      __threadfence();
      if (atomicAdd(&g_done, 1u) == gridDim.x - 1) { g_ticket = 0; g_done = 0; }
    } else if (warp == 2 && lane == 0) {
      for (uint32_t n = 0;; n++) {
        int task;
        mbar_wait(tfull0 + 8 * (n & 3), (n >> 2) & 1);
        asm volatile("ld.shared.b32 %0, [%1];" : "=r"(task) : "r"(tbox + 4 * (n & 3)) : "memory");
        if (task < 0) break;
        mbar_wait(sig0 + 8 * (n & 3), (n >> 2) & 1);
        mbar_arrive(tempty0 + 8 * (n & 3));
        __threadfence();
        const int b = ((task >> 3) & 3) * 2 + ((task >> 2) & 1), h = (task >> 5) & 31, blk = (task >> 10) & 1;
        asm volatile("st.release.gpu.global.u32 [%0], %1;" :: "l"(&g_flag[(blk * NB + b) * NH + h]), "r"(6u) : "memory");
      }
    }
  } else {
    asm volatile("setmaxnreg.inc.sync.aligned.u32 240;");
    const int wg = (warp >> 2) - 1, w = warp & 3, tid = threadIdx.x & 127;
    Cons r; r.base = sbase; r.full0 = full0; r.it = 0; r.lane = lane;
    uint32_t qf[48];
    STAMP(0, 0);
    for (uint32_t n = 0;; n++) {
      int task;
      mbar_wait(tfull0 + 8 * (n & 3), (n >> 2) & 1);
      asm volatile("ld.shared.b32 %0, [%1];" : "=r"(task) : "r"(tbox + 4 * (n & 3)) : "memory");
      task = __shfl_sync(0xffffffffu, task, 0);
      if (lane == 0) mbar_arrive(tempty0 + 8 * (n & 3));
      if (task < 0) break;
      const int type = task & 3, bsel = (task >> 2) & 1, pr = (task >> 3) & 3, h = (task >> 5) & 31, blk = (task >> 10) & 1;
      const int b = pr * 2 + bsel;
      bool valid;
      int row8;
      if (type != 2) {
        qproj(r, qf, park, type == 0, wg, tid);
        if (wg == 1 && type == 0) asm volatile("bar.arrive 1, 256;" ::: "memory");
        valid = (wg == 0 || w < 2);
        row8 = wg * 8 + w * 2;
      } else {
        if (wg == 0) {
          asm volatile("bar.sync 1, 256;" ::: "memory");
#pragma unroll
          for (int ks = 0; ks < 12; ks++)
            asm volatile("ld.shared.v4.b32 {%0, %1, %2, %3}, [%4];" : "=r"(qf[4 * ks]), "=r"(qf[4 * ks + 1]), "=r"(qf[4 * ks + 2]), "=r"(qf[4 * ks + 3]) : "r"(park + (ks * 128 + tid) * 16) : "memory");
        }
        valid = (wg == 0 || w >= 2);
        row8 = wg == 0 ? 4 + w * 2 : (w - 2) * 2;
      }
      uint32_t* st = reinterpret_cast<uint32_t*>(g_stash) + (size_t)((blk * NH + h) * NB + b) * 9216 + row8 * 256;
      attention(r, qf, valid, st, sig0 + 8 * (n & 3), wg);
      STAMP(n + 1, task);
    }
  }
}

constexpr int NS2 = 9;
constexpr int SMEM2_BYTES = NS2 * SLOT + 1024 + 256;
#define A2 5
#define CHA2 0, 16, 32
#define CHA3 0, 11, 21, 32
#define CHB4 0, 8, 16, 23, 32
constexpr int N_CLUSTERS2 = 2 * A2 + 3 * (10 - A2) + 40;

__device__ __forceinline__ void tma_3d_mc(uint32_t dst, const CUtensorMap* m, int c0, int c1, int c2, uint32_t bar) {
  asm volatile("cp.async.bulk.tensor.3d.shared::cluster.global.mbarrier::complete_tx::bytes.multicast::cluster [%0], [%1, {%3, %4, %5}], [%2], %6;"
               :: "r"(dst), "l"(m), "r"(bar), "r"(c0), "r"(c1), "r"(c2), "h"((uint16_t)3) : "memory");
}
__device__ __forceinline__ void bulk_load_mc(uint32_t dst, const void* src, uint32_t bytes, uint32_t bar) {
  asm volatile("cp.async.bulk.shared::cluster.global.mbarrier::complete_tx::bytes.multicast::cluster [%0], [%1], %2, [%3], %4;"
               :: "r"(dst), "l"(src), "r"(bytes), "r"(bar), "h"((uint16_t)3) : "memory");
}
__device__ __forceinline__ void cluster_sync() {
  asm volatile("barrier.cluster.arrive.release.aligned;\nbarrier.cluster.wait.acquire.aligned;" ::: "memory");
}

__global__ void __cluster_dims__(2, 1, 1) __launch_bounds__(384, 1) oproj_kernel(const __grid_constant__ Maps maps, __nv_bfloat16* out) {
  extern __shared__ uint8_t smem_raw[];
  const uint32_t sbase = (smem_u32(smem_raw) + 1023u) & ~1023u;
  const uint32_t full0 = sbase + NS2 * SLOT, empty0 = full0 + 8 * NS2;
  const int warp = __shfl_sync(0xffffffffu, threadIdx.x >> 5, 0), lane = threadIdx.x & 31;
  const int rank = blockIdx.x & 1;
  const uint32_t ent = maps.otab[blockIdx.x >> 1];
  const int blk = ent & 1, tp = (ent >> 1) & 15, h0 = (ent >> 5) & 63, nh = (ent >> 11) & 63;
  const unsigned int nch = (ent >> 17) & 15;
  const bool fin = (ent >> 21) & 1;
  const bool share_o = tp < 8;
  const int pr = share_o ? (tp >> 1) : (tp - 8) * 2 + rank, nt = share_o ? (tp & 1) * 2 + rank : 4;
  if (threadIdx.x == 0) {
    for (int i = 0; i < NS2; i++) { mbar_init(full0 + 8 * i, 1); mbar_init(empty0 + 8 * i, 16); }
    asm volatile("fence.mbarrier_init.release.cluster;" ::: "memory");
  }
  cluster_sync();

  if (warp < 4) {
    if (warp == 0) {
      uint32_t s = 0, ph = 1;
      const uint8_t* src = reinterpret_cast<const uint8_t*>(g_stash) + (size_t)((blk * NH + h0) * NB + pr * 2) * 36864;
      const int fb = share_o ? rank : (lane >> 4);
      const unsigned int* fl = &g_flag[(blk * NB + pr * 2 + fb) * NH + h0 + (lane & 15)];
      const bool watch = (lane & 15) < nh;
      unsigned int ready = 0;
#pragma unroll 1
      for (int hh = 0; hh < nh; hh++) {
        const int krow = (h0 + hh) * DH;
#pragma unroll 1
        for (int q = 0; q < 5; q++) {
          if (q == 1 && !((ready >> hh) & 1)) {
            for (int spin = 0; spin < (1 << 22); spin++) {
              const unsigned int m = __ballot_sync(0xffffffffu, !watch || ld_acquire(fl) == 6u);
              ready = m & (m >> 16);
              if ((ready >> hh) & 1) break;
              __nanosleep(32);
            }
            asm volatile("fence.proxy.async;" ::: "memory");
          }
          if (lane == 0) {
            mbar_wait(empty0 + 8 * s, ph);
            mbar_expect_tx(full0 + 8 * s, SLOT);
            const uint32_t dst = sbase + s * SLOT, bar = full0 + 8 * s;
            if (q == 0 || q == 3) {
              if (share_o) tma_3d(dst, &maps.wo[blk], 0, krow + (q ? 96 : 0), nt * 2, bar);
              else tma_3d_mc(dst + rank * 12288, &maps.wo1[blk], 0, krow + (q ? 96 : 0), nt * 2 + rank, bar);
            } else {
              const int kc = q == 4 ? 2 : q - 1;
              if (share_o) bulk_load_mc(dst + rank * 12288, src + rank * 36864 + kc * 12288, 12288, bar);
              else { bulk_load(dst, src + kc * 12288, 12288, bar); bulk_load(dst + 12288, src + 36864 + kc * 12288, 12288, bar); }
            }
          }
          __syncwarp();
          if (++s == NS2) { s = 0; ph ^= 1; }
        }
        src += NB * 36864;
      }
      if (fin && lane == 0) {
        const int tile = (blk * 4 + pr) * 5 + nt;
        for (int spin = 0; spin < (1 << 22) && ld_acquire(&g_tile_cnt[tile]) != (nch - 1) * 8; spin++) __nanosleep(32);
        g_tile_cnt[tile] = 0;
        asm volatile("fence.proxy.async;" ::: "memory");
        const uint8_t* ps = reinterpret_cast<const uint8_t*>(g_part) + (size_t)tile * 4 * SLOT;
#pragma unroll 1
        for (int q = 0; q < 4; q++) {
          mbar_wait(empty0 + 8 * s, ph);
          mbar_expect_tx(full0 + 8 * s, SLOT);
          bulk_load(sbase + s * SLOT, ps + q * SLOT, SLOT, full0 + 8 * s);
          if (++s == NS2) { s = 0; ph ^= 1; }
        }
      }
      __syncwarp();
      asm volatile("griddepcontrol.wait;" ::: "memory");
      unsigned int d = 0;
      if (lane == 0) d = atomicAdd(&g_done2, 1u);
      if (__shfl_sync(0xffffffffu, d, 0) == gridDim.x - 1) {
        for (int i = lane; i < 2 * NB * NH; i += 32) g_flag[i] = 0;
        if (lane == 0) g_done2 = 0;
      }
    }
  } else {
    const int wg = (warp >> 2) - 1, w = warp & 3, tid = threadIdx.x & 127;
    uint32_t peer_empty0;
    asm volatile("mapa.shared::cluster.u32 %0, %1, %2;" : "=r"(peer_empty0) : "r"(empty0), "r"(rank ^ 1));
    uint32_t s = 0, ph = 0;
    auto next = [&](uint32_t& slot) -> uint32_t {
      slot = s;
      mbar_wait(full0 + 8 * s, ph);
      if (++s == NS2) { s = 0; ph ^= 1; }
      return sbase + slot * SLOT;
    };
    auto release = [&](uint32_t slot) {
      if (lane == 0) {
        mbar_arrive(empty0 + 8 * slot);
        asm volatile("mbarrier.arrive.shared::cluster.b64 _, [%0];" :: "r"(peer_empty0 + 8 * slot) : "memory");
      }
    };
    const int tile = (blk * 4 + pr) * 5 + nt;
    float acc[96];
    uint32_t pw1 = 0, po2 = 0;
    for (int hh = 0; hh < nh; hh++) {
      uint32_t sw0, so0, so1, sw1, so2;
      const uint64_t dw0 = desc_mnmajor_sw128<1024>(next(sw0) + wg * 12288);
      const uint64_t do0 = desc_kmajor_nosw(next(so0));
      wg_fence();
#pragma unroll
      for (int ks = 0; ks < 4; ks++) wgmma_st_n192_t0(acc, dw0 + ks * 128, do0 + ks * 16, (hh > 0 || ks > 0) ? 1 : 0);
      wg_commit();
      if (hh > 0) { wg_wait<1>(); release(pw1); release(po2); }
      const uint64_t do1 = desc_kmajor_nosw(next(so1));
      const uint64_t dw1 = desc_mnmajor_sw128<1024>(next(sw1) + wg * 12288);
      wg_fence();
      wgmma_st_n192_t0(acc, dw0 + 4 * 128, do1, 1);
      wgmma_st_n192_t0(acc, dw0 + 5 * 128, do1 + 16, 1);
      wgmma_st_n192_t0(acc, dw1, do1 + 32, 1);
      wgmma_st_n192_t0(acc, dw1 + 128, do1 + 48, 1);
      wg_commit();
      wg_wait<1>(); release(so0);
      const uint64_t do2 = desc_kmajor_nosw(next(so2));
      wg_fence();
#pragma unroll
      for (int ks = 0; ks < 4; ks++) wgmma_st_n192_t0(acc, dw1 + (2 + ks) * 128, do2 + ks * 16, 1);
      wg_commit();
      wg_wait<1>(); release(sw0); release(so1);
      pw1 = sw1; po2 = so2;
    }
    wg_wait<0>();
    touch(acc);
    float4* part = g_part + (size_t)(tile * 2 + wg) * 24 * 128 + tid;
    if (!fin) {
#pragma unroll
      for (int j = 0; j < 24; j++)
        asm volatile("red.global.add.v4.f32 [%0], {%1, %2, %3, %4};" :: "l"(part + j * 128), "f"(acc[4 * j]), "f"(acc[4 * j + 1]), "f"(acc[4 * j + 2]), "f"(acc[4 * j + 3]) : "memory");
      __threadfence();
      __syncwarp();
      if (lane == 0) atomicAdd(&g_tile_cnt[tile], 1u);
    } else {
      release(pw1); release(po2);
      asm volatile("bar.sync 3, 256;" ::: "memory");
      uint32_t sl, pa[4];
#pragma unroll
      for (int q = 0; q < 4; q++) {
        pa[q] = sbase + s * SLOT;
        if ((q >> 1) == wg) next(sl); else if (++s == NS2) { s = 0; ph ^= 1; }
      }
      const uint32_t s1 = s + 1 == NS2 ? 0 : s + 1;
      const uint32_t stg = sbase + (wg ? s1 : s) * SLOT;
      const int q = lane & 3;
      const bool odd = (lane >> 2) & 1;
      const int r8 = 2 * q + (odd ? 1 : 0);
      const uint32_t w0a = stg + r8 * 128 + (((2 * w) ^ r8) << 4) + (lane >> 3) * 4, w1a = stg + r8 * 128 + (((2 * w + 1) ^ r8) << 4) + (lane >> 3) * 4;
      const uint32_t p0 = (wg ? pa[2] : pa[0]) + tid * 16, p1 = (wg ? pa[3] : pa[1]) + tid * 16;
#pragma unroll
      for (int j = 0; j < 24; j++) {
        float4 e;
        asm volatile("ld.shared.v4.f32 {%0, %1, %2, %3}, [%4];" : "=f"(e.x), "=f"(e.y), "=f"(e.z), "=f"(e.w) : "r"((j < 12 ? p0 : p1) + (j % 12) * 2048) : "memory");
        const float x = acc[4 * j] + e.x, y = acc[4 * j + 1] + e.y, z = acc[4 * j + 2] + e.z, u = acc[4 * j + 3] + e.w;
        const float rx = __shfl_xor_sync(0xffffffffu, odd ? x : y, 4), rz = __shfl_xor_sync(0xffffffffu, odd ? z : u, 4);
        asm volatile("st.shared.b32 [%0], %1;" :: "r"(w0a + j * 1024), "r"(odd ? pack_bf16(rx, y) : pack_bf16(x, rx)) : "memory");
        asm volatile("st.shared.b32 [%0], %1;" :: "r"(w1a + j * 1024), "r"(odd ? pack_bf16(rz, u) : pack_bf16(z, rz)) : "memory");
      }
      asm volatile("bar.sync %0, 128;" :: "r"(1 + wg) : "memory");
      uint8_t* ob = reinterpret_cast<uint8_t*>(out + (size_t)(pr * 192) * (2 * DM) + blk * DM + nt * 128 + wg * 64);
#pragma unroll
      for (int i = 0; i < 12; i++) {
        const int row = i * 16 + (tid >> 3), ck = tid & 7;
        uint4 v;
        asm volatile("ld.shared.v4.b32 {%0, %1, %2, %3}, [%4];" : "=r"(v.x), "=r"(v.y), "=r"(v.z), "=r"(v.w) : "r"(stg + row * 128 + ((ck ^ (row & 7)) << 4)) : "memory");
        *reinterpret_cast<uint4*>(ob + (size_t)row * (4 * DM) + ck * 16) = v;
      }
#pragma unroll
      for (int j = 0; j < 24; j++) __stcg(part + j * 128, make_float4(0.f, 0.f, 0.f, 0.f));
    }
  }
  cluster_sync();
}

typedef CUresult (*EncodeFn)(CUtensorMap*, CUtensorMapDataType, cuuint32_t, void*, const cuuint64_t*, const cuuint64_t*, const cuuint32_t*, const cuuint32_t*,
                             CUtensorMapInterleave, CUtensorMapSwizzle, CUtensorMapL2promotion, CUtensorMapFloatOOBfill);

void make_map(EncodeFn fn, CUtensorMap* m, const void* ptr, int rank, const uint64_t* dims, const uint64_t* strides, const uint32_t* box) {
  cuuint32_t es[4] = {1, 1, 1, 1};
  fn(m, CU_TENSOR_MAP_DATA_TYPE_BFLOAT16, rank, const_cast<void*>(ptr), dims, strides, box, es, CU_TENSOR_MAP_INTERLEAVE_NONE,
     CU_TENSOR_MAP_SWIZZLE_128B, CU_TENSOR_MAP_L2_PROMOTION_L2_256B, CU_TENSOR_MAP_FLOAT_OOB_FILL_NONE);
}

}

extern "C" void kernel_launch(void* const* d_in, const int* in_sizes, int n_in, void* d_out, int out_size) {
  static Maps maps;
  static const void* cached[10] = {nullptr};
  static bool init = false;
  static int grid = NCTA;
  bool same = init;
  for (int i = 0; i < 10; i++) same = same && (cached[i] == d_in[i]);
  if (!same) {
    void* fnp = nullptr;
    cudaDriverEntryPointQueryResult qr;
    cudaGetDriverEntryPoint("cuTensorMapEncodeTiled", &fnp, cudaEnableDefault, &qr);
    EncodeFn fn = (EncodeFn)fnp;
    for (int b = 0; b < 2; b++) {
      const void* x = d_in[5 * b + 0]; const void* k = d_in[5 * b + 1]; const void* v = d_in[5 * b + 2];
      const void* wq = d_in[5 * b + 3]; const void* wo = d_in[5 * b + 4];
      { uint64_t d[2] = {DM, NB * SQ}; uint64_t s[1] = {DM * 2}; uint32_t bx[2] = {64, 192}; make_map(fn, &maps.x[b], x, 2, d, s, bx);
        uint32_t b1[2] = {64, 96}; make_map(fn, &maps.x1[b], x, 2, d, s, b1); }
      { uint64_t d[4] = {64, 8, NH * DH / 64, DM / 8}; uint64_t s[3] = {NH * DH * 2, 128, 8 * NH * DH * 2}; uint32_t bx[4] = {64, 8, 3, 8}; make_map(fn, &maps.wq[b], wq, 4, d, s, bx); }
      { uint64_t d[4] = {64, 8, 3, (uint64_t)NB * NH * SK / 8}; uint64_t s[3] = {DH * 2, 128, 8 * DH * 2}; uint32_t bx[4] = {64, 8, 3, 8};
        make_map(fn, &maps.k[b], k, 4, d, s, bx); make_map(fn, &maps.v[b], v, 4, d, s, bx); }
      { uint64_t d[3] = {64, NH * DH, DM / 64}; uint64_t s[2] = {DM * 2, 128}; uint32_t bx[3] = {64, 96, 2}; make_map(fn, &maps.wo[b], wo, 3, d, s, bx);
        uint32_t b1[3] = {64, 96, 1}; make_map(fn, &maps.wo1[b], wo, 3, d, s, b1); }
    }
    {
      const int a2[3] = {CHA2}, a3[4] = {CHA3}, b4[5] = {CHB4};
      int n = 0;
      auto add = [&](int blk, int tp, int h0, int h1, int nch) { maps.otab[n++] = blk | (tp << 1) | (h0 << 5) | ((h1 - h0) << 11) | (nch << 17) | ((h1 == NH) << 21); };
      for (int c = 0; c < 2; c++) for (int tp = 0; tp < A2; tp++) add(0, tp, a2[c], a2[c + 1], 2);
      for (int c = 0; c < 3; c++) for (int tp = A2; tp < 10; tp++) add(0, tp, a3[c], a3[c + 1], 3);
      for (int c = 0; c < 4; c++) for (int tp = 0; tp < 10; tp++) add(1, tp, b4[c], b4[c + 1], 4);
    }
    cudaFuncSetAttribute(attn_kernel, cudaFuncAttributeMaxDynamicSharedMemorySize, SMEM_BYTES);
    cudaFuncSetAttribute(oproj_kernel, cudaFuncAttributeMaxDynamicSharedMemorySize, SMEM2_BYTES);
    int dev = 0, sms = NCTA;
    cudaGetDevice(&dev);
    cudaDeviceGetAttribute(&sms, cudaDevAttrMultiProcessorCount, dev);
    grid = sms < NCTA ? sms : NCTA;
    for (int i = 0; i < 10; i++) cached[i] = d_in[i];
    init = true;
  }
  attn_kernel<<<grid, 384, SMEM_BYTES>>>(maps);
  cudaLaunchConfig_t cfg = {};
  cfg.gridDim = dim3(2 * N_CLUSTERS2); cfg.blockDim = dim3(384); cfg.dynamicSmemBytes = SMEM2_BYTES; cfg.stream = cudaStreamPerThread;
  cudaLaunchAttribute at[1];
  at[0].id = cudaLaunchAttributeProgrammaticStreamSerialization; at[0].val.programmaticStreamSerializationAllowed = PDL;
  cfg.attrs = at; cfg.numAttrs = 1;
  cudaLaunchKernelEx(&cfg, oproj_kernel, maps, (__nv_bfloat16*)d_out);
}
```

```cpp
#include <cuda_runtime.h>
#include <cuda_bf16.h>
#include <cuda.h>
#include <stdint.h>

namespace {

constexpr int NB = 8, SQ = 96, DM = 640, NH = 32, SK = 512, DH = 192;
constexpr int SLOT = 24576;
constexpr int NSLOT = 8;
constexpr int SMEM_BYTES = NSLOT * SLOT + SLOT   + 1024   + 256  ;

#define NCTA 132
#define N_ATT 66
#define NPAIR 224
#define FETCH_AHEAD 3
#define KV_INFLIGHT 8
#define WQ_EF 0
#define PDL 1
constexpr int N_TICKETS = NPAIR + 2 * (256 - NPAIR) + (NCTA - N_ATT) / 2;

struct Maps { CUtensorMap x[2], x1[2], wq[2], k[2], v[2], wo[2]; uint32_t otab[140]; };

__device__ uint4 g_stash[2 * NH * NB * 2304];
__device__ float4 g_part[2][40 * 2 * 24 * 128];
__device__ unsigned int g_epoch;
__device__ unsigned int g_tile_cnt[40];
__device__ unsigned int g_flag[2 * NB * NH];
__device__ unsigned int g_ticket, g_done, g_done2;

#define STAMP(i, tk)

__device__ __forceinline__ uint32_t smem_u32(const void* p) { return (uint32_t)__cvta_generic_to_shared(p); }
__device__ __forceinline__ void mbar_init(uint32_t bar, int cnt) { asm volatile("mbarrier.init.shared::cta.b64 [%0], %1;" :: "r"(bar), "r"(cnt) : "memory"); }
__device__ __forceinline__ void mbar_expect_tx(uint32_t bar, uint32_t bytes) { asm volatile("mbarrier.arrive.expect_tx.shared::cta.b64 _, [%0], %1;" :: "r"(bar), "r"(bytes) : "memory"); }
__device__ __forceinline__ void mbar_arrive(uint32_t bar) { asm volatile("mbarrier.arrive.shared::cta.b64 _, [%0];" :: "r"(bar) : "memory"); }
__device__ __forceinline__ void mbar_wait(uint32_t bar, uint32_t parity) {
  asm volatile("{\n.reg .pred p;\nWAIT_%=:\nmbarrier.try_wait.parity.shared::cta.b64 p, [%0], %1;\n@p bra DONE_%=;\nbra WAIT_%=;\nDONE_%=:\n}" :: "r"(bar), "r"(parity) : "memory");
}
__device__ __forceinline__ void tma_2d(uint32_t dst, const CUtensorMap* m, int c0, int c1, uint32_t bar) {
  asm volatile("cp.async.bulk.tensor.2d.shared::cluster.global.mbarrier::complete_tx::bytes [%0], [%1, {%3, %4}], [%2];"
               :: "r"(dst), "l"(m), "r"(bar), "r"(c0), "r"(c1) : "memory");
}
__device__ __forceinline__ void tma_3d(uint32_t dst, const CUtensorMap* m, int c0, int c1, int c2, uint32_t bar) {
  asm volatile("cp.async.bulk.tensor.3d.shared::cluster.global.mbarrier::complete_tx::bytes [%0], [%1, {%3, %4, %5}], [%2];"
               :: "r"(dst), "l"(m), "r"(bar), "r"(c0), "r"(c1), "r"(c2) : "memory");
}
__device__ __forceinline__ void tma_4d(uint32_t dst, const CUtensorMap* m, int c2, int c3, uint32_t bar) {
  asm volatile("cp.async.bulk.tensor.4d.shared::cluster.global.mbarrier::complete_tx::bytes [%0], [%1, {%3, %3, %4, %5}], [%2];"
               :: "r"(dst), "l"(m), "r"(bar), "r"(0), "r"(c2), "r"(c3) : "memory");
}
__device__ __forceinline__ void tma_4d_hint(uint32_t dst, const CUtensorMap* m, int c2, int c3, uint32_t bar, uint64_t pol) {
  asm volatile("cp.async.bulk.tensor.4d.shared::cluster.global.mbarrier::complete_tx::bytes.L2::cache_hint [%0], [%1, {%3, %3, %4, %5}], [%2], %6;"
               :: "r"(dst), "l"(m), "r"(bar), "r"(0), "r"(c2), "r"(c3), "l"(pol) : "memory");
}
__device__ __forceinline__ void bulk_load(uint32_t dst, const void* src, uint32_t bytes, uint32_t bar) {
  asm volatile("cp.async.bulk.shared::cluster.global.mbarrier::complete_tx::bytes [%0], [%1], %2, [%3];" :: "r"(dst), "l"(src), "r"(bytes), "r"(bar) : "memory");
}
__device__ __forceinline__ void wg_fence() { asm volatile("wgmma.fence.sync.aligned;" ::: "memory"); }
__device__ __forceinline__ void wg_commit() { asm volatile("wgmma.commit_group.sync.aligned;" ::: "memory"); }
template <int N> __device__ __forceinline__ void wg_wait() { asm volatile("wgmma.wait_group.sync.aligned %0;" :: "n"(N) : "memory"); }
template <int N> __device__ __forceinline__ void touch(float (&d)[N]) {
#pragma unroll
  for (int i = 0; i < N; i++) asm volatile("" : "+f"(d[i]) :: "memory");
}
template <int N> __device__ __forceinline__ void touch_u(uint32_t (&d)[N]) {
#pragma unroll
  for (int i = 0; i < N; i++) asm volatile("" : "+r"(d[i]) :: "memory");
}
__device__ __forceinline__ float ex2(float x) { float y; asm("ex2.approx.ftz.f32 %0, %1;" : "=f"(y) : "f"(x)); return y; }
__device__ __forceinline__ uint32_t pack_bf16(float lo, float hi) { uint32_t r; asm("cvt.rn.bf16x2.f32 %0, %1, %2;" : "=r"(r) : "f"(hi), "f"(lo)); return r; }

constexpr uint64_t DESC_SW128 = (uint64_t)1 << 62;
__device__ __forceinline__ uint64_t desc_kmajor_sw128(uint32_t addr) {
  return DESC_SW128 | ((uint64_t)(1024 >> 4) << 32) | ((uint64_t)1 << 16) | (uint64_t)((addr & 0x3FFFF) >> 4);
}
__device__ __forceinline__ uint64_t desc_k_il(uint32_t addr) {
  return DESC_SW128 | ((uint64_t)(3072 >> 4) << 32) | ((uint64_t)1 << 16) | (uint64_t)((addr & 0x3FFFF) >> 4);
}
__device__ __forceinline__ uint64_t desc_mn_il(uint32_t addr) {
  return DESC_SW128 | ((uint64_t)(3072 >> 4) << 32) | ((uint64_t)(1024 >> 4) << 16) | (uint64_t)((addr & 0x3FFFF) >> 4);
}
template <int LBO> __device__ __forceinline__ uint64_t desc_mnmajor_sw128(uint32_t addr) {
  return DESC_SW128 | ((uint64_t)(1024 >> 4) << 32) | ((uint64_t)(LBO >> 4) << 16) | (uint64_t)((addr & 0x3FFFF) >> 4);
}
__device__ __forceinline__ uint64_t desc_kmajor_nosw(uint32_t addr) {
  return ((uint64_t)(1024 >> 4) << 32) | ((uint64_t)(128 >> 4) << 16) | (uint64_t)((addr & 0x3FFFF) >> 4);
}

__device__ __forceinline__ void wgmma_rs_n64_t0(float (&d)[32], uint32_t a0, uint32_t a1, uint32_t a2, uint32_t a3, uint64_t descB, int scaleD) {
  asm volatile("{\n.reg .pred p;\nsetp.ne.b32 p, %37, 0;\n"
    "wgmma.mma_async.sync.aligned.m64n64k16.f32.bf16.bf16 "
    "{%0, %1, %2, %3, %4, %5, %6, %7, %8, %9, %10, %11, %12, %13, %14, %15, %16, %17, %18, %19, %20, %21, %22, %23, %24, %25, %26, %27, %28, %29, %30, %31}, "
    "{%32, %33, %34, %35}, %36, p, 1, 1, 0;\n}\n"
    : "+f"(d[0]), "+f"(d[1]), "+f"(d[2]), "+f"(d[3]), "+f"(d[4]), "+f"(d[5]), "+f"(d[6]), "+f"(d[7]), "+f"(d[8]), "+f"(d[9]), "+f"(d[10]), "+f"(d[11]), "+f"(d[12]), "+f"(d[13]), "+f"(d[14]), "+f"(d[15]), "+f"(d[16]), "+f"(d[17]), "+f"(d[18]), "+f"(d[19]), "+f"(d[20]), "+f"(d[21]), "+f"(d[22]), "+f"(d[23]), "+f"(d[24]), "+f"(d[25]), "+f"(d[26]), "+f"(d[27]), "+f"(d[28]), "+f"(d[29]), "+f"(d[30]), "+f"(d[31])
    : "r"(a0), "r"(a1), "r"(a2), "r"(a3), "l"(descB), "r"(scaleD));
}
__device__ __forceinline__ void wgmma_rs_n192_t1(float (&d)[96], uint32_t a0, uint32_t a1, uint32_t a2, uint32_t a3, uint64_t descB, int scaleD) {
  asm volatile("{\n.reg .pred p;\nsetp.ne.b32 p, %101, 0;\n"
    "wgmma.mma_async.sync.aligned.m64n192k16.f32.bf16.bf16 "
    "{%0, %1, %2, %3, %4, %5, %6, %7, %8, %9, %10, %11, %12, %13, %14, %15, %16, %17, %18, %19, %20, %21, %22, %23, %24, %25, %26, %27, %28, %29, %30, %31, %32, %33, %34, %35, %36, %37, %38, %39, %40, %41, %42, %43, %44, %45, %46, %47, %48, %49, %50, %51, %52, %53, %54, %55, %56, %57, %58, %59, %60, %61, %62, %63, %64, %65, %66, %67, %68, %69, %70, %71, %72, %73, %74, %75, %76, %77, %78, %79, %80, %81, %82, %83, %84, %85, %86, %87, %88, %89, %90, %91, %92, %93, %94, %95}, "
    "{%96, %97, %98, %99}, %100, p, 1, 1, 1;\n}\n"
    : "+f"(d[0]), "+f"(d[1]), "+f"(d[2]), "+f"(d[3]), "+f"(d[4]), "+f"(d[5]), "+f"(d[6]), "+f"(d[7]), "+f"(d[8]), "+f"(d[9]), "+f"(d[10]), "+f"(d[11]), "+f"(d[12]), "+f"(d[13]), "+f"(d[14]), "+f"(d[15]), "+f"(d[16]), "+f"(d[17]), "+f"(d[18]), "+f"(d[19]), "+f"(d[20]), "+f"(d[21]), "+f"(d[22]), "+f"(d[23]), "+f"(d[24]), "+f"(d[25]), "+f"(d[26]), "+f"(d[27]), "+f"(d[28]), "+f"(d[29]), "+f"(d[30]), "+f"(d[31]), "+f"(d[32]), "+f"(d[33]), "+f"(d[34]), "+f"(d[35]), "+f"(d[36]), "+f"(d[37]), "+f"(d[38]), "+f"(d[39]), "+f"(d[40]), "+f"(d[41]), "+f"(d[42]), "+f"(d[43]), "+f"(d[44]), "+f"(d[45]), "+f"(d[46]), "+f"(d[47]), "+f"(d[48]), "+f"(d[49]), "+f"(d[50]), "+f"(d[51]), "+f"(d[52]), "+f"(d[53]), "+f"(d[54]), "+f"(d[55]), "+f"(d[56]), "+f"(d[57]), "+f"(d[58]), "+f"(d[59]), "+f"(d[60]), "+f"(d[61]), "+f"(d[62]), "+f"(d[63]), "+f"(d[64]), "+f"(d[65]), "+f"(d[66]), "+f"(d[67]), "+f"(d[68]), "+f"(d[69]), "+f"(d[70]), "+f"(d[71]), "+f"(d[72]), "+f"(d[73]), "+f"(d[74]), "+f"(d[75]), "+f"(d[76]), "+f"(d[77]), "+f"(d[78]), "+f"(d[79]), "+f"(d[80]), "+f"(d[81]), "+f"(d[82]), "+f"(d[83]), "+f"(d[84]), "+f"(d[85]), "+f"(d[86]), "+f"(d[87]), "+f"(d[88]), "+f"(d[89]), "+f"(d[90]), "+f"(d[91]), "+f"(d[92]), "+f"(d[93]), "+f"(d[94]), "+f"(d[95])
    : "r"(a0), "r"(a1), "r"(a2), "r"(a3), "l"(descB), "r"(scaleD));
}
__device__ __forceinline__ void wgmma_ss_n192_t1(float (&d)[96], uint64_t descA, uint64_t descB, int scaleD) {
  asm volatile("{\n.reg .pred p;\nsetp.ne.b32 p, %98, 0;\n"
    "wgmma.mma_async.sync.aligned.m64n192k16.f32.bf16.bf16 "
    "{%0, %1, %2, %3, %4, %5, %6, %7, %8, %9, %10, %11, %12, %13, %14, %15, %16, %17, %18, %19, %20, %21, %22, %23, %24, %25, %26, %27, %28, %29, %30, %31, %32, %33, %34, %35, %36, %37, %38, %39, %40, %41, %42, %43, %44, %45, %46, %47, %48, %49, %50, %51, %52, %53, %54, %55, %56, %57, %58, %59, %60, %61, %62, %63, %64, %65, %66, %67, %68, %69, %70, %71, %72, %73, %74, %75, %76, %77, %78, %79, %80, %81, %82, %83, %84, %85, %86, %87, %88, %89, %90, %91, %92, %93, %94, %95}, "
    "%96, %97, p, 1, 1, 0, 1;\n}\n"
    : "+f"(d[0]), "+f"(d[1]), "+f"(d[2]), "+f"(d[3]), "+f"(d[4]), "+f"(d[5]), "+f"(d[6]), "+f"(d[7]), "+f"(d[8]), "+f"(d[9]), "+f"(d[10]), "+f"(d[11]), "+f"(d[12]), "+f"(d[13]), "+f"(d[14]), "+f"(d[15]), "+f"(d[16]), "+f"(d[17]), "+f"(d[18]), "+f"(d[19]), "+f"(d[20]), "+f"(d[21]), "+f"(d[22]), "+f"(d[23]), "+f"(d[24]), "+f"(d[25]), "+f"(d[26]), "+f"(d[27]), "+f"(d[28]), "+f"(d[29]), "+f"(d[30]), "+f"(d[31]), "+f"(d[32]), "+f"(d[33]), "+f"(d[34]), "+f"(d[35]), "+f"(d[36]), "+f"(d[37]), "+f"(d[38]), "+f"(d[39]), "+f"(d[40]), "+f"(d[41]), "+f"(d[42]), "+f"(d[43]), "+f"(d[44]), "+f"(d[45]), "+f"(d[46]), "+f"(d[47]), "+f"(d[48]), "+f"(d[49]), "+f"(d[50]), "+f"(d[51]), "+f"(d[52]), "+f"(d[53]), "+f"(d[54]), "+f"(d[55]), "+f"(d[56]), "+f"(d[57]), "+f"(d[58]), "+f"(d[59]), "+f"(d[60]), "+f"(d[61]), "+f"(d[62]), "+f"(d[63]), "+f"(d[64]), "+f"(d[65]), "+f"(d[66]), "+f"(d[67]), "+f"(d[68]), "+f"(d[69]), "+f"(d[70]), "+f"(d[71]), "+f"(d[72]), "+f"(d[73]), "+f"(d[74]), "+f"(d[75]), "+f"(d[76]), "+f"(d[77]), "+f"(d[78]), "+f"(d[79]), "+f"(d[80]), "+f"(d[81]), "+f"(d[82]), "+f"(d[83]), "+f"(d[84]), "+f"(d[85]), "+f"(d[86]), "+f"(d[87]), "+f"(d[88]), "+f"(d[89]), "+f"(d[90]), "+f"(d[91]), "+f"(d[92]), "+f"(d[93]), "+f"(d[94]), "+f"(d[95])
    : "l"(descA), "l"(descB), "r"(scaleD));
}
__device__ __forceinline__ void wgmma_ss_n64_t1(float (&d)[32], uint64_t descA, uint64_t descB, int scaleD) {
  asm volatile("{\n.reg .pred p;\nsetp.ne.b32 p, %34, 0;\n"
    "wgmma.mma_async.sync.aligned.m64n64k16.f32.bf16.bf16 "
    "{%0, %1, %2, %3, %4, %5, %6, %7, %8, %9, %10, %11, %12, %13, %14, %15, %16, %17, %18, %19, %20, %21, %22, %23, %24, %25, %26, %27, %28, %29, %30, %31}, "
    "%32, %33, p, 1, 1, 0, 1;\n}\n"
    : "+f"(d[0]), "+f"(d[1]), "+f"(d[2]), "+f"(d[3]), "+f"(d[4]), "+f"(d[5]), "+f"(d[6]), "+f"(d[7]), "+f"(d[8]), "+f"(d[9]), "+f"(d[10]), "+f"(d[11]), "+f"(d[12]), "+f"(d[13]), "+f"(d[14]), "+f"(d[15]), "+f"(d[16]), "+f"(d[17]), "+f"(d[18]), "+f"(d[19]), "+f"(d[20]), "+f"(d[21]), "+f"(d[22]), "+f"(d[23]), "+f"(d[24]), "+f"(d[25]), "+f"(d[26]), "+f"(d[27]), "+f"(d[28]), "+f"(d[29]), "+f"(d[30]), "+f"(d[31])
    : "l"(descA), "l"(descB), "r"(scaleD));
}
__device__ __forceinline__ void wgmma_ss_n32_t1(float (&d)[16], uint64_t descA, uint64_t descB, int scaleD) {
  asm volatile("{\n.reg .pred p;\nsetp.ne.b32 p, %18, 0;\n"
    "wgmma.mma_async.sync.aligned.m64n32k16.f32.bf16.bf16 "
    "{%0, %1, %2, %3, %4, %5, %6, %7, %8, %9, %10, %11, %12, %13, %14, %15}, "
    "%16, %17, p, 1, 1, 0, 1;\n}\n"
    : "+f"(d[0]), "+f"(d[1]), "+f"(d[2]), "+f"(d[3]), "+f"(d[4]), "+f"(d[5]), "+f"(d[6]), "+f"(d[7]), "+f"(d[8]), "+f"(d[9]), "+f"(d[10]), "+f"(d[11]), "+f"(d[12]), "+f"(d[13]), "+f"(d[14]), "+f"(d[15])
    : "l"(descA), "l"(descB), "r"(scaleD));
}
__device__ __forceinline__ void wgmma_st_n192_t0(float (&d)[96], uint64_t descA, uint64_t descB, int scaleD) {
  asm volatile("{\n.reg .pred p;\nsetp.ne.b32 p, %98, 0;\n"
    "wgmma.mma_async.sync.aligned.m64n192k16.f32.bf16.bf16 "
    "{%0, %1, %2, %3, %4, %5, %6, %7, %8, %9, %10, %11, %12, %13, %14, %15, %16, %17, %18, %19, %20, %21, %22, %23, %24, %25, %26, %27, %28, %29, %30, %31, %32, %33, %34, %35, %36, %37, %38, %39, %40, %41, %42, %43, %44, %45, %46, %47, %48, %49, %50, %51, %52, %53, %54, %55, %56, %57, %58, %59, %60, %61, %62, %63, %64, %65, %66, %67, %68, %69, %70, %71, %72, %73, %74, %75, %76, %77, %78, %79, %80, %81, %82, %83, %84, %85, %86, %87, %88, %89, %90, %91, %92, %93, %94, %95}, "
    "%96, %97, p, 1, 1, 1, 0;\n}\n"
    : "+f"(d[0]), "+f"(d[1]), "+f"(d[2]), "+f"(d[3]), "+f"(d[4]), "+f"(d[5]), "+f"(d[6]), "+f"(d[7]), "+f"(d[8]), "+f"(d[9]), "+f"(d[10]), "+f"(d[11]), "+f"(d[12]), "+f"(d[13]), "+f"(d[14]), "+f"(d[15]), "+f"(d[16]), "+f"(d[17]), "+f"(d[18]), "+f"(d[19]), "+f"(d[20]), "+f"(d[21]), "+f"(d[22]), "+f"(d[23]), "+f"(d[24]), "+f"(d[25]), "+f"(d[26]), "+f"(d[27]), "+f"(d[28]), "+f"(d[29]), "+f"(d[30]), "+f"(d[31]), "+f"(d[32]), "+f"(d[33]), "+f"(d[34]), "+f"(d[35]), "+f"(d[36]), "+f"(d[37]), "+f"(d[38]), "+f"(d[39]), "+f"(d[40]), "+f"(d[41]), "+f"(d[42]), "+f"(d[43]), "+f"(d[44]), "+f"(d[45]), "+f"(d[46]), "+f"(d[47]), "+f"(d[48]), "+f"(d[49]), "+f"(d[50]), "+f"(d[51]), "+f"(d[52]), "+f"(d[53]), "+f"(d[54]), "+f"(d[55]), "+f"(d[56]), "+f"(d[57]), "+f"(d[58]), "+f"(d[59]), "+f"(d[60]), "+f"(d[61]), "+f"(d[62]), "+f"(d[63]), "+f"(d[64]), "+f"(d[65]), "+f"(d[66]), "+f"(d[67]), "+f"(d[68]), "+f"(d[69]), "+f"(d[70]), "+f"(d[71]), "+f"(d[72]), "+f"(d[73]), "+f"(d[74]), "+f"(d[75]), "+f"(d[76]), "+f"(d[77]), "+f"(d[78]), "+f"(d[79]), "+f"(d[80]), "+f"(d[81]), "+f"(d[82]), "+f"(d[83]), "+f"(d[84]), "+f"(d[85]), "+f"(d[86]), "+f"(d[87]), "+f"(d[88]), "+f"(d[89]), "+f"(d[90]), "+f"(d[91]), "+f"(d[92]), "+f"(d[93]), "+f"(d[94]), "+f"(d[95])
    : "l"(descA), "l"(descB), "r"(scaleD));
}

__device__ __forceinline__ unsigned int ld_acquire(const unsigned int* p) { unsigned int v; asm volatile("ld.acquire.gpu.global.u32 %0, [%1];" : "=r"(v) : "l"(p) : "memory"); return v; }

struct Cons {
  uint32_t base, full0;
  uint32_t it;
  int lane;
  __device__ __forceinline__ uint32_t wait(uint32_t slot, uint32_t u) const { mbar_wait(full0 + slot * 8, (u >> 3) & 1); return base + slot * SLOT; }
  __device__ __forceinline__ uint32_t wait(uint32_t u) const { return wait(u & 7, u); }
  __device__ __forceinline__ void release(uint32_t slot) const { if (lane == 0) mbar_arrive(full0 + 64 + (slot & 7) * 8); }
};

__device__ __forceinline__ int ticket_task(int ticket) {
  int u = ticket, f = 0;
  if (ticket >= N_ATT) {
    if (ticket < NCTA) { const int s = ticket - N_ATT; u = N_ATT + (s >> 1); f = 1 | ((s & 1) << 2); }
    else {
      u = ticket - (NCTA - N_ATT) / 2;
      if (u >= NPAIR) { const int s = u - NPAIR; u = NPAIR + (s >> 1); f = 1 | ((s & 1) << 2); }
    }
  }
  const int hh = u & 7, pr = (u >> 3) & 3, g = (u >> 5) & 3, blk = u >> 7;
  return f | (pr << 3) | ((g * 8 + hh) << 5) | (blk << 10);
}

__device__ __forceinline__ void qproj(Cons& r, uint32_t (&qf)[48], uint32_t park, bool pair, int wg, int tid) {
  float acc[96];
  float acx[32];
  float acy[16];
  for (int c = 0; c < 10; c++) {
    const uint32_t sx = r.it;
    const uint32_t xa = r.wait(sx), wa = r.wait(sx + 1);
    const uint64_t da = desc_kmajor_sw128(xa + wg * 8192), d2 = desc_kmajor_sw128(xa + 2 * 8192);
    const uint64_t db = desc_mn_il(wa), dbx = desc_mn_il(wa + wg * 1024), dby = desc_mn_il(wa + 2048 + wg * 64);
    if (pair) {
      wg_fence();
#pragma unroll
      for (int ks = 0; ks < 4; ks++) {
        const int sc = (c > 0 || ks > 0) ? 1 : 0;
        wgmma_ss_n192_t1(acc, da + ks * 2, db + ks * 384, sc);
        wgmma_ss_n64_t1(acx, d2 + ks * 2, dbx + ks * 384, sc);
        wgmma_ss_n32_t1(acy, d2 + ks * 2, dby + ks * 384, sc);
      }
      wg_commit();
    } else {
      wg_fence();
#pragma unroll
      for (int ks = 0; ks < 4; ks++)
        wgmma_ss_n192_t1(acc, da + ks * 2, db + ks * 384, (c > 0 || ks > 0) ? 1 : 0);
      wg_commit();
    }
    if (c > 0) { wg_wait<1>(); r.release((sx + 6) & 7); r.release((sx + 7) & 7); }
    r.it += 2;
  }
  wg_wait<0>();
  touch(acc); touch(acx); touch(acy);
  r.release((r.it + 6) & 7); r.release((r.it + 7) & 7);
  if (pair) {
#pragma unroll
    for (int ks = 0; ks < 4; ks++) {
      uint32_t a0 = pack_bf16(acx[8 * ks + 0], acx[8 * ks + 1]), a1 = pack_bf16(acx[8 * ks + 2], acx[8 * ks + 3]);
      uint32_t a2 = pack_bf16(acx[8 * ks + 4], acx[8 * ks + 5]), a3 = pack_bf16(acx[8 * ks + 6], acx[8 * ks + 7]);
      asm volatile("st.shared.v4.b32 [%0], {%1, %2, %3, %4};" :: "r"(park + ((wg * 4 + ks) * 128 + tid) * 16), "r"(a0), "r"(a1), "r"(a2), "r"(a3) : "memory");
    }
#pragma unroll
    for (int ks = 0; ks < 2; ks++) {
      uint32_t a0 = pack_bf16(acy[8 * ks + 0], acy[8 * ks + 1]), a1 = pack_bf16(acy[8 * ks + 2], acy[8 * ks + 3]);
      uint32_t a2 = pack_bf16(acy[8 * ks + 4], acy[8 * ks + 5]), a3 = pack_bf16(acy[8 * ks + 6], acy[8 * ks + 7]);
      asm volatile("st.shared.v4.b32 [%0], {%1, %2, %3, %4};" :: "r"(park + ((8 + wg * 2 + ks) * 128 + tid) * 16), "r"(a0), "r"(a1), "r"(a2), "r"(a3) : "memory");
    }
  }
#pragma unroll
  for (int i = 0; i < 48; i++) qf[i] = pack_bf16(acc[2 * i], acc[2 * i + 1]);
}

__device__ __forceinline__ void sched_sync(int wg) { asm volatile("bar.sync %0, 256;" :: "r"(2 + wg) : "memory"); }
__device__ __forceinline__ void sched_arrive(int wg) { asm volatile("bar.arrive %0, 256;" :: "r"(3 - wg) : "memory"); }

__device__ __forceinline__ void issue_qk(float (&s)[32], const uint32_t (&qf)[48], uint64_t dk) {
#pragma unroll
  for (int ks = 0; ks < 12; ks++)
    wgmma_rs_n64_t0(s, qf[4 * ks], qf[4 * ks + 1], qf[4 * ks + 2], qf[4 * ks + 3], dk + ((ks >> 2) * 64 + (ks & 3) * 2), ks > 0);
  wg_commit();
}
__device__ __forceinline__ void attention(Cons& r, const uint32_t (&qf)[48], bool valid, uint32_t* dst, uint32_t sig, int wg) {
  constexpr float CS = 0.07216878364870322f * 1.4426950408889634f;
  const int lane = r.lane;
  float o[96];
  float s[32];
  uint32_t pa[8], pb[8];
  float m0 = -INFINITY, m1 = -INFINITY, l0 = 0.f, l1 = 0.f, al0 = 1.f, al1 = 1.f;
  bool resc = false;
#pragma unroll
  for (int i = 0; i < 8; i++) { pa[i] = 0; pb[i] = 0; }

  auto row_max = [&]() {
    float x0 = fmaxf(s[0], s[1]), x1 = fmaxf(s[2], s[3]), y0 = fmaxf(s[4], s[5]), y1 = fmaxf(s[6], s[7]);
#pragma unroll
    for (int i = 2; i < 8; i += 2) {
      x0 = fmaxf(x0, fmaxf(s[4 * i], s[4 * i + 1])); x1 = fmaxf(x1, fmaxf(s[4 * i + 2], s[4 * i + 3]));
      y0 = fmaxf(y0, fmaxf(s[4 * i + 4], s[4 * i + 5])); y1 = fmaxf(y1, fmaxf(s[4 * i + 6], s[4 * i + 7]));
    }
    x0 = fmaxf(x0, y0); x1 = fmaxf(x1, y1);
    x0 = fmaxf(x0, __shfl_xor_sync(0xffffffffu, x0, 1)); x1 = fmaxf(x1, __shfl_xor_sync(0xffffffffu, x1, 1));
    x0 = fmaxf(x0, __shfl_xor_sync(0xffffffffu, x0, 2)); x1 = fmaxf(x1, __shfl_xor_sync(0xffffffffu, x1, 2));
    resc = __any_sync(0xffffffffu, (x0 - m0) * CS > 8.0f || (x1 - m1) * CS > 8.0f);
    if (resc) {
      const float n0 = fmaxf(m0, x0), n1 = fmaxf(m1, x1);
      al0 = ex2((m0 - n0) * CS); al1 = ex2((m1 - n1) * CS);
      m0 = n0; m1 = n1;
      l0 *= al0; l1 *= al1;
    }
  };
  auto exps = [&](uint32_t (&p)[8], int h) {
    const float c0 = m0 * CS, c1 = m1 * CS;
    float t0 = 0.f, t1 = 0.f;
#pragma unroll
    for (int i = 0; i < 4; i++) {
      const int k = 16 * h + 4 * i;
      const float e0 = ex2(fmaf(s[k], CS, -c0)), e1 = ex2(fmaf(s[k + 1], CS, -c0));
      const float e2 = ex2(fmaf(s[k + 2], CS, -c1)), e3 = ex2(fmaf(s[k + 3], CS, -c1));
      t0 += e0 + e1; t1 += e2 + e3;
      p[2 * i] = pack_bf16(e0, e1); p[2 * i + 1] = pack_bf16(e2, e3);
    }
    l0 += t0; l1 += t1;
  };
  auto pv_a = [&](uint64_t dv, int first) {
    wgmma_rs_n192_t1(o, pa[0], pa[1], pa[2], pa[3], dv, first ? 0 : 1);
    wgmma_rs_n192_t1(o, pa[4], pa[5], pa[6], pa[7], dv + 384, 1);
    wg_commit();
  };
  auto pv_b = [&](uint64_t dv) {
    wgmma_rs_n192_t1(o, pb[0], pb[1], pb[2], pb[3], dv + 768, 1);
    wgmma_rs_n192_t1(o, pb[4], pb[5], pb[6], pb[7], dv + 1152, 1);
    wg_commit();
  };

  if (wg == 1) sched_arrive(1);
  {
    const uint32_t sk = r.it & 7;
    const uint64_t dk = desc_k_il(r.wait(sk, r.it));
    sched_sync(wg);
    wg_fence();
    issue_qk(s, qf, dk);
    sched_arrive(wg);
    wg_wait<0>();
    touch(s);
    r.release(sk);
    if (valid) { row_max(); exps(pa, 0); exps(pb, 1); }
  }
  for (int j = 0; j < 7; j++) {
    const uint32_t u = r.it;
    const uint32_t sv = (u + 1) & 7, sk = (u + 2) & 7;
    const uint64_t dk = desc_k_il(r.wait(sk, u + 2));
    const uint64_t dv = desc_mn_il(r.wait(sv, u + 1));
    sched_sync(wg);
    wg_fence();
    issue_qk(s, qf, dk);
    pv_a(dv, j == 0);
    pv_b(dv);
    sched_arrive(wg);
    wg_wait<2>();
    touch(s);
    r.release(sk);
    if (valid) row_max();
    wg_wait<1>();
    touch_u(pa);
    if (valid) exps(pa, 0);
    touch_u(pa);
    wg_wait<0>();
    touch(o); touch_u(pb);
    r.release(sv);
    if (valid) exps(pb, 1);
    if (resc) {
#pragma unroll
      for (int i = 0; i < 24; i++) { o[4 * i] *= al0; o[4 * i + 1] *= al0; o[4 * i + 2] *= al1; o[4 * i + 3] *= al1; }
    }
    touch_u(pb);
    r.it += 2;
  }
  {
    const uint32_t sv = (r.it + 1) & 7;
    const uint64_t dv = desc_mn_il(r.wait(sv, r.it + 1));
    sched_sync(wg);
    wg_fence();
    pv_a(dv, 0);
    pv_b(dv);
    if (wg == 0) sched_arrive(0);
    wg_wait<0>();
    touch(o); touch_u(pa); touch_u(pb);
    r.release(sv);
    r.it += 2;
  }
  if (valid) {
    l0 += __shfl_xor_sync(0xffffffffu, l0, 1); l1 += __shfl_xor_sync(0xffffffffu, l1, 1);
    l0 += __shfl_xor_sync(0xffffffffu, l0, 2); l1 += __shfl_xor_sync(0xffffffffu, l1, 2);
    const float i0 = 1.0f / l0, i1 = 1.0f / l1;
#pragma unroll
    for (int kc = 0; kc < 24; kc++) {
      dst[(kc >> 3) * 3072 + (kc & 7) * 32 + lane] = pack_bf16(o[4 * kc] * i0, o[4 * kc + 1] * i0);
      dst[(kc >> 3) * 3072 + 256 + (kc & 7) * 32 + lane] = pack_bf16(o[4 * kc + 2] * i1, o[4 * kc + 3] * i1);
    }
    __syncwarp();
    if (lane == 0) mbar_arrive(sig);
  }
}

__global__ void __launch_bounds__(384, 1) attn_kernel(const __grid_constant__ Maps maps) {
  extern __shared__ uint8_t smem_raw[];
  const uint32_t sbase = (smem_u32(smem_raw) + 1023u) & ~1023u;
  const uint32_t park = sbase + NSLOT * SLOT;
  const uint32_t bars = park + SLOT;
  const uint32_t full0 = bars, empty0 = bars + 64;
  const uint32_t tfull0 = bars + 128, tempty0 = bars + 160, sig0 = bars + 192, tbox = bars + 224, sreq = bars + 240;
  const int warp = __shfl_sync(0xffffffffu, threadIdx.x >> 5, 0), lane = threadIdx.x & 31;
  if (threadIdx.x == 0) {
    for (int i = 0; i < NSLOT; i++) { mbar_init(full0 + 8 * i, 1); mbar_init(empty0 + 8 * i, 8); }
    for (int i = 0; i < 4; i++) { mbar_init(tfull0 + 8 * i, 1); mbar_init(tempty0 + 8 * i, 10); mbar_init(sig0 + 8 * i, 6); }
    mbar_init(sreq, 1);
    asm volatile("fence.mbarrier_init.release.cluster;" ::: "memory");
  }
  __syncthreads();
  asm volatile("griddepcontrol.launch_dependents;");

  if (warp < 4) {
    asm volatile("setmaxnreg.dec.sync.aligned.u32 24;");
    if (warp == 0 && lane == 0) {
      uint64_t pol; asm volatile("createpolicy.fractional.L2::evict_first.b64 %0, 1.0;" : "=l"(pol));
      uint32_t u = 0;
      auto acquire = [&](uint32_t bytes) -> uint32_t {
        const uint32_t s = u & 7;
        mbar_wait(empty0 + 8 * s, ((u >> 3) & 1) ^ 1);
        mbar_expect_tx(full0 + 8 * s, bytes);
        u++;
        return s;
      };
      for (uint32_t n = 0;; n++) {
        int task;
        mbar_wait(tfull0 + 8 * (n & 3), (n >> 2) & 1);
        asm volatile("ld.shared.b32 %0, [%1];" : "=r"(task) : "r"(tbox + 4 * (n & 3)) : "memory");
        mbar_arrive(tempty0 + 8 * (n & 3));
        if (task < 0) break;
        const int type = task & 3, bsel = (task >> 2) & 1, pr = (task >> 3) & 3, h = (task >> 5) & 31, blk = (task >> 10) & 1;
        if (type != 2) {
          const CUtensorMap* mx = type ? &maps.x1[blk] : &maps.x[blk];
#pragma unroll 1
          for (int c = 0; c < 10; c++) {
            uint32_t s = acquire(type ? SLOT / 2 : SLOT);
            tma_2d(sbase + s * SLOT, mx, c * 64, pr * 192 + bsel * 96, full0 + 8 * s);
            s = acquire(SLOT);
            if (WQ_EF) tma_4d_hint(sbase + s * SLOT, &maps.wq[blk], h * 3, c * 8, full0 + 8 * s, pol);
            else tma_4d(sbase + s * SLOT, &maps.wq[blk], h * 3, c * 8, full0 + 8 * s);
          }
        }
        int rg = (((pr * 2 + bsel) * NH + h) * SK) >> 3;
#pragma unroll 1
        for (int j = 0; j < 8; j++) {
          if (j == 8 - FETCH_AHEAD) mbar_arrive(sreq);
          if (KV_INFLIGHT < 8 && u >= KV_INFLIGHT) mbar_wait(full0 + 8 * ((u - KV_INFLIGHT) & 7), ((u - KV_INFLIGHT) >> 3) & 1);
          uint32_t s = acquire(SLOT);
          tma_4d_hint(sbase + s * SLOT, &maps.k[blk], 0, rg, full0 + 8 * s, pol);
          if (KV_INFLIGHT < 8 && u >= KV_INFLIGHT) mbar_wait(full0 + 8 * ((u - KV_INFLIGHT) & 7), ((u - KV_INFLIGHT) >> 3) & 1);
          s = acquire(SLOT);
          tma_4d_hint(sbase + s * SLOT, &maps.v[blk], 0, rg, full0 + 8 * s, pol);
          rg += 8;
        }
      }
    } else if (warp == 1 && lane == 0) {
      int task = ticket_task(blockIdx.x);
      for (uint32_t n = 0;; n++) {
        mbar_wait(tempty0 + 8 * (n & 3), ((n >> 2) & 1) ^ 1);
        asm volatile("st.shared.b32 [%0], %1;" :: "r"(tbox + 4 * (n & 3)), "r"(task) : "memory");
        mbar_arrive(tfull0 + 8 * (n & 3));
        if (task < 0) break;
        if ((task & 3) == 0) {
          task |= 2 | 4;
        } else {
          mbar_wait(sreq, n & 1);
          const unsigned int tk = atomicAdd(&g_ticket, 1u) + gridDim.x;
          task = tk < (unsigned)N_TICKETS ? ticket_task((int)tk) : -1;
          continue;
        }
        mbar_wait(sreq, n & 1);
      }
      __threadfence();
      if (atomicAdd(&g_done, 1u) == gridDim.x - 1) { g_ticket = 0; g_done = 0; }
    } else if (warp == 2 && lane == 0) {
      for (uint32_t n = 0;; n++) {
        int task;
        mbar_wait(tfull0 + 8 * (n & 3), (n >> 2) & 1);
        asm volatile("ld.shared.b32 %0, [%1];" : "=r"(task) : "r"(tbox + 4 * (n & 3)) : "memory");
        if (task < 0) break;
        mbar_wait(sig0 + 8 * (n & 3), (n >> 2) & 1);
        mbar_arrive(tempty0 + 8 * (n & 3));
        __threadfence();
        const int b = ((task >> 3) & 3) * 2 + ((task >> 2) & 1), h = (task >> 5) & 31, blk = (task >> 10) & 1;
        asm volatile("st.release.gpu.global.u32 [%0], %1;" :: "l"(&g_flag[(blk * NB + b) * NH + h]), "r"(6u) : "memory");
      }
    }
  } else {
    asm volatile("setmaxnreg.inc.sync.aligned.u32 240;");
    const int wg = (warp >> 2) - 1, w = warp & 3, tid = threadIdx.x & 127;
    Cons r; r.base = sbase; r.full0 = full0; r.it = 0; r.lane = lane;
    uint32_t qf[48];
    STAMP(0, 0);
    for (uint32_t n = 0;; n++) {
      int task;
      mbar_wait(tfull0 + 8 * (n & 3), (n >> 2) & 1);
      asm volatile("ld.shared.b32 %0, [%1];" : "=r"(task) : "r"(tbox + 4 * (n & 3)) : "memory");
      task = __shfl_sync(0xffffffffu, task, 0);
      if (lane == 0) mbar_arrive(tempty0 + 8 * (n & 3));
      if (task < 0) break;
      const int type = task & 3, bsel = (task >> 2) & 1, pr = (task >> 3) & 3, h = (task >> 5) & 31, blk = (task >> 10) & 1;
      const int b = pr * 2 + bsel;
      bool valid;
      int row8;
      if (type != 2) {
        qproj(r, qf, park, type == 0, wg, tid);
        if (wg == 1 && type == 0) asm volatile("bar.arrive 1, 256;" ::: "memory");
        valid = (wg == 0 || w < 2);
        row8 = wg * 8 + w * 2;
      } else {
        if (wg == 0) {
          asm volatile("bar.sync 1, 256;" ::: "memory");
#pragma unroll
          for (int ks = 0; ks < 12; ks++)
            asm volatile("ld.shared.v4.b32 {%0, %1, %2, %3}, [%4];" : "=r"(qf[4 * ks]), "=r"(qf[4 * ks + 1]), "=r"(qf[4 * ks + 2]), "=r"(qf[4 * ks + 3]) : "r"(park + (ks * 128 + tid) * 16) : "memory");
        }
        valid = (wg == 0 || w >= 2);
        row8 = wg == 0 ? 4 + w * 2 : (w - 2) * 2;
      }
      uint32_t* st = reinterpret_cast<uint32_t*>(g_stash) + (size_t)((blk * NH + h) * NB + b) * 9216 + row8 * 256;
      attention(r, qf, valid, st, sig0 + 8 * (n & 3), wg);
      STAMP(n + 1, task);
    }
  }
}

constexpr int NS2 = 9;
constexpr int SMEM2_BYTES = NS2 * SLOT + 1024 + 256;
#define A2 8
#define CHA2 0, 15, 32
#define CHA3 0, 11, 21, 32
#define CHB4 0, 8, 16, 23, 32
constexpr int N_CTA2 = 2 * A2 + 3 * (20 - A2) + 80;

__global__ void __launch_bounds__(384, 1) oproj_kernel(const __grid_constant__ Maps maps, __nv_bfloat16* out) {
  extern __shared__ uint8_t smem_raw[];
  const uint32_t sbase = (smem_u32(smem_raw) + 1023u) & ~1023u;
  const uint32_t full0 = sbase + NS2 * SLOT, empty0 = full0 + 8 * NS2;
  const int warp = __shfl_sync(0xffffffffu, threadIdx.x >> 5, 0), lane = threadIdx.x & 31;
  const uint32_t ent = maps.otab[blockIdx.x];
  const int blk = ent & 1, tl = (ent >> 1) & 31, h0 = (ent >> 6) & 63, nh = (ent >> 12) & 63;
  const unsigned int nch = (ent >> 18) & 15;
  const bool fin = (ent >> 22) & 1;
  const int pr = tl & 3, nt = tl >> 2;
  if (threadIdx.x == 0) {
    for (int i = 0; i < NS2; i++) { mbar_init(full0 + 8 * i, 1); mbar_init(empty0 + 8 * i, 8); }
    asm volatile("st.shared.b32 [%0], %1;" :: "r"(empty0 + 8 * NS2), "r"(ld_acquire(&g_epoch) & 1u) : "memory");
    asm volatile("fence.mbarrier_init.release.cluster;" ::: "memory");
  }
  __syncthreads();
  uint32_t par;
  asm volatile("ld.shared.b32 %0, [%1];" : "=r"(par) : "r"(empty0 + 8 * NS2) : "memory");

  if (warp < 4) {
    if (warp == 0) {
      uint32_t s = 0, ph = 1;
      const uint8_t* src = reinterpret_cast<const uint8_t*>(g_stash) + (size_t)((blk * NH + h0) * NB + pr * 2) * 36864;
      const unsigned int* fl = &g_flag[(blk * NB + pr * 2 + (lane >> 4)) * NH + h0 + (lane & 15)];
      unsigned int ready = 0;
#pragma unroll 1
      for (int hh = 0; hh < nh; hh++) {
        const int krow = (h0 + hh) * DH;
#pragma unroll 1
        for (int q = 0; q < 5; q++) {
          if (q == 1 && hh == 16) ready = 0;
          if (q == 1 && !((ready >> (hh & 15)) & 1)) {
            const bool watch = (hh & 16) + (lane & 15) < nh;
            for (int spin = 0; spin < (1 << 22); spin++) {
              const unsigned int m = __ballot_sync(0xffffffffu, !watch || ld_acquire(fl + (hh & 16)) == 6u);
              ready = m & (m >> 16);
              if ((ready >> (hh & 15)) & 1) break;
              __nanosleep(32);
            }
            asm volatile("fence.proxy.async;" ::: "memory");
          }
          if (lane == 0) {
            mbar_wait(empty0 + 8 * s, ph);
            mbar_expect_tx(full0 + 8 * s, SLOT);
            const uint32_t dst = sbase + s * SLOT, bar = full0 + 8 * s;
            if (q == 0 || q == 3) {
              tma_3d(dst, &maps.wo[blk], 0, krow + (q ? 96 : 0), nt * 2, bar);
            } else {
              const int kc = q == 4 ? 2 : q - 1;
              bulk_load(dst, src + kc * 12288, 12288, bar);
              bulk_load(dst + 12288, src + 36864 + kc * 12288, 12288, bar);
            }
          }
          __syncwarp();
          if (++s == NS2) { s = 0; ph ^= 1; }
        }
        src += NB * 36864;
      }
      if (fin && lane == 0) {
        const int tile = (blk * 4 + pr) * 5 + nt;
        for (int spin = 0; spin < (1 << 22) && ld_acquire(&g_tile_cnt[tile]) != (nch - 1) * 8; spin++) __nanosleep(32);
        g_tile_cnt[tile] = 0;
        asm volatile("fence.proxy.async;" ::: "memory");
        const uint8_t* ps = reinterpret_cast<const uint8_t*>(g_part[par]) + (size_t)tile * 4 * SLOT;
#pragma unroll 1
        for (int q = 0; q < 4; q++) {
          mbar_wait(empty0 + 8 * s, ph);
          mbar_expect_tx(full0 + 8 * s, SLOT);
          bulk_load(sbase + s * SLOT, ps + q * SLOT, SLOT, full0 + 8 * s);
          if (++s == NS2) { s = 0; ph ^= 1; }
        }
      }
      __syncwarp();
      asm volatile("griddepcontrol.wait;" ::: "memory");
      unsigned int d = 0;
      if (lane == 0) d = atomicAdd(&g_done2, 1u);
      if (__shfl_sync(0xffffffffu, d, 0) == gridDim.x - 1) {
        for (int i = lane; i < 2 * NB * NH; i += 32) g_flag[i] = 0;
        if (lane == 0) { g_done2 = 0; g_epoch = par ^ 1; }
      }
    }
  } else {
    const int wg = (warp >> 2) - 1, w = warp & 3, tid = threadIdx.x & 127;
    uint32_t s = 0, ph = 0;
    auto next = [&](uint32_t& slot) -> uint32_t {
      slot = s;
      mbar_wait(full0 + 8 * s, ph);
      if (++s == NS2) { s = 0; ph ^= 1; }
      return sbase + slot * SLOT;
    };
    auto release = [&](uint32_t slot) { if (lane == 0) mbar_arrive(empty0 + 8 * slot); };
    const int tile = (blk * 4 + pr) * 5 + nt;
    float acc[96];
    uint32_t pw1 = 0, po2 = 0;
    for (int hh = 0; hh < nh; hh++) {
      uint32_t sw0, so0, so1, sw1, so2;
      const uint64_t dw0 = desc_mnmajor_sw128<1024>(next(sw0) + wg * 12288);
      const uint64_t do0 = desc_kmajor_nosw(next(so0));
      wg_fence();
#pragma unroll
      for (int ks = 0; ks < 4; ks++) wgmma_st_n192_t0(acc, dw0 + ks * 128, do0 + ks * 16, (hh > 0 || ks > 0) ? 1 : 0);
      wg_commit();
      if (hh > 0) { wg_wait<1>(); release(pw1); release(po2); }
      const uint64_t do1 = desc_kmajor_nosw(next(so1));
      const uint64_t dw1 = desc_mnmajor_sw128<1024>(next(sw1) + wg * 12288);
      wg_fence();
      wgmma_st_n192_t0(acc, dw0 + 4 * 128, do1, 1);
      wgmma_st_n192_t0(acc, dw0 + 5 * 128, do1 + 16, 1);
      wgmma_st_n192_t0(acc, dw1, do1 + 32, 1);
      wgmma_st_n192_t0(acc, dw1 + 128, do1 + 48, 1);
      wg_commit();
      wg_wait<1>(); release(so0);
      const uint64_t do2 = desc_kmajor_nosw(next(so2));
      wg_fence();
#pragma unroll
      for (int ks = 0; ks < 4; ks++) wgmma_st_n192_t0(acc, dw1 + (2 + ks) * 128, do2 + ks * 16, 1);
      wg_commit();
      wg_wait<1>(); release(sw0); release(so1);
      pw1 = sw1; po2 = so2;
    }
    wg_wait<0>();
    touch(acc);
    float4* part = g_part[par] + (size_t)(tile * 2 + wg) * 24 * 128 + tid;
    if (!fin) {
#pragma unroll
      for (int j = 0; j < 24; j++)
        asm volatile("red.global.add.v4.f32 [%0], {%1, %2, %3, %4};" :: "l"(part + j * 128), "f"(acc[4 * j]), "f"(acc[4 * j + 1]), "f"(acc[4 * j + 2]), "f"(acc[4 * j + 3]) : "memory");
      __threadfence();
      __syncwarp();
      if (lane == 0) atomicAdd(&g_tile_cnt[tile], 1u);
      for (int i = (int)(ent >> 23) * 256 + (int)threadIdx.x - 128; i < 40 * 2 * 24 * 128; i += (N_CTA2 - 40) * 256)
        __stcg(g_part[par ^ 1] + i, make_float4(0.f, 0.f, 0.f, 0.f));
    } else {
      release(pw1); release(po2);
      asm volatile("bar.sync 3, 256;" ::: "memory");
      uint32_t sl, pa[4];
#pragma unroll
      for (int q = 0; q < 4; q++) {
        pa[q] = sbase + s * SLOT;
        if ((q >> 1) == wg) next(sl); else if (++s == NS2) { s = 0; ph ^= 1; }
      }
      const uint32_t s1 = s + 1 == NS2 ? 0 : s + 1;
      const uint32_t stg = sbase + (wg ? s1 : s) * SLOT;
      const int q = lane & 3;
      const bool odd = (lane >> 2) & 1;
      const int r8 = 2 * q + (odd ? 1 : 0);
      const uint32_t w0a = stg + r8 * 128 + (((2 * w) ^ r8) << 4) + (lane >> 3) * 4, w1a = stg + r8 * 128 + (((2 * w + 1) ^ r8) << 4) + (lane >> 3) * 4;
      const uint32_t p0 = (wg ? pa[2] : pa[0]) + tid * 16, p1 = (wg ? pa[3] : pa[1]) + tid * 16;
#pragma unroll
      for (int j = 0; j < 24; j++) {
        float4 e;
        asm volatile("ld.shared.v4.f32 {%0, %1, %2, %3}, [%4];" : "=f"(e.x), "=f"(e.y), "=f"(e.z), "=f"(e.w) : "r"((j < 12 ? p0 : p1) + (j % 12) * 2048) : "memory");
        const float x = acc[4 * j] + e.x, y = acc[4 * j + 1] + e.y, z = acc[4 * j + 2] + e.z, u = acc[4 * j + 3] + e.w;
        const float rx = __shfl_xor_sync(0xffffffffu, odd ? x : y, 4), rz = __shfl_xor_sync(0xffffffffu, odd ? z : u, 4);
        asm volatile("st.shared.b32 [%0], %1;" :: "r"(w0a + j * 1024), "r"(odd ? pack_bf16(rx, y) : pack_bf16(x, rx)) : "memory");
        asm volatile("st.shared.b32 [%0], %1;" :: "r"(w1a + j * 1024), "r"(odd ? pack_bf16(rz, u) : pack_bf16(z, rz)) : "memory");
      }
      asm volatile("bar.sync %0, 128;" :: "r"(1 + wg) : "memory");
      uint8_t* ob = reinterpret_cast<uint8_t*>(out + (size_t)(pr * 192) * (2 * DM) + blk * DM + nt * 128 + wg * 64);
#pragma unroll
      for (int i = 0; i < 12; i++) {
        const int row = i * 16 + (tid >> 3), ck = tid & 7;
        uint4 v;
        asm volatile("ld.shared.v4.b32 {%0, %1, %2, %3}, [%4];" : "=r"(v.x), "=r"(v.y), "=r"(v.z), "=r"(v.w) : "r"(stg + row * 128 + ((ck ^ (row & 7)) << 4)) : "memory");
        *reinterpret_cast<uint4*>(ob + (size_t)row * (4 * DM) + ck * 16) = v;
      }
    }
  }
}

typedef CUresult (*EncodeFn)(CUtensorMap*, CUtensorMapDataType, cuuint32_t, void*, const cuuint64_t*, const cuuint64_t*, const cuuint32_t*, const cuuint32_t*,
                             CUtensorMapInterleave, CUtensorMapSwizzle, CUtensorMapL2promotion, CUtensorMapFloatOOBfill);

void make_map(EncodeFn fn, CUtensorMap* m, const void* ptr, int rank, const uint64_t* dims, const uint64_t* strides, const uint32_t* box) {
  cuuint32_t es[4] = {1, 1, 1, 1};
  fn(m, CU_TENSOR_MAP_DATA_TYPE_BFLOAT16, rank, const_cast<void*>(ptr), dims, strides, box, es, CU_TENSOR_MAP_INTERLEAVE_NONE,
     CU_TENSOR_MAP_SWIZZLE_128B, CU_TENSOR_MAP_L2_PROMOTION_L2_256B, CU_TENSOR_MAP_FLOAT_OOB_FILL_NONE);
}

}

extern "C" void kernel_launch(void* const* d_in, const int* in_sizes, int n_in, void* d_out, int out_size) {
  static Maps maps;
  static const void* cached[10] = {nullptr};
  static bool init = false;
  static int grid = NCTA;
  bool same = init;
  for (int i = 0; i < 10; i++) same = same && (cached[i] == d_in[i]);
  if (!same) {
    void* fnp = nullptr;
    cudaDriverEntryPointQueryResult qr;
    cudaGetDriverEntryPoint("cuTensorMapEncodeTiled", &fnp, cudaEnableDefault, &qr);
    EncodeFn fn = (EncodeFn)fnp;
    for (int b = 0; b < 2; b++) {
      const void* x = d_in[5 * b + 0]; const void* k = d_in[5 * b + 1]; const void* v = d_in[5 * b + 2];
      const void* wq = d_in[5 * b + 3]; const void* wo = d_in[5 * b + 4];
      { uint64_t d[2] = {DM, NB * SQ}; uint64_t s[1] = {DM * 2}; uint32_t bx[2] = {64, 192}; make_map(fn, &maps.x[b], x, 2, d, s, bx);
        uint32_t b1[2] = {64, 96}; make_map(fn, &maps.x1[b], x, 2, d, s, b1); }
      { uint64_t d[4] = {64, 8, NH * DH / 64, DM / 8}; uint64_t s[3] = {NH * DH * 2, 128, 8 * NH * DH * 2}; uint32_t bx[4] = {64, 8, 3, 8}; make_map(fn, &maps.wq[b], wq, 4, d, s, bx); }
      { uint64_t d[4] = {64, 8, 3, (uint64_t)NB * NH * SK / 8}; uint64_t s[3] = {DH * 2, 128, 8 * DH * 2}; uint32_t bx[4] = {64, 8, 3, 8};
        make_map(fn, &maps.k[b], k, 4, d, s, bx); make_map(fn, &maps.v[b], v, 4, d, s, bx); }
      { uint64_t d[3] = {64, NH * DH, DM / 64}; uint64_t s[2] = {DM * 2, 128}; uint32_t bx[3] = {64, 96, 2}; make_map(fn, &maps.wo[b], wo, 3, d, s, bx); }
    }
    {
      const int a2[3] = {CHA2}, a3[4] = {CHA3}, b4[5] = {CHB4};
      int n = 0, nz = 0;
      auto add = [&](int blk, int tl, int h0, int h1, int nch) { maps.otab[n++] = blk | (tl << 1) | (h0 << 6) | ((h1 - h0) << 12) | (nch << 18) | ((h1 == NH) << 22) | ((h1 == NH ? 0u : (unsigned)nz++) << 23); };
      for (int c = 0; c < 2; c++) for (int tp = 0; tp < A2; tp++) add(0, tp, a2[c], a2[c + 1], 2);
      for (int c = 0; c < 3; c++) for (int tp = A2; tp < 20; tp++) add(0, tp, a3[c], a3[c + 1], 3);
      for (int c = 0; c < 4; c++) for (int tp = 0; tp < 20; tp++) add(1, tp, b4[c], b4[c + 1], 4);
    }
    cudaFuncSetAttribute(attn_kernel, cudaFuncAttributeMaxDynamicSharedMemorySize, SMEM_BYTES);
    cudaFuncSetAttribute(oproj_kernel, cudaFuncAttributeMaxDynamicSharedMemorySize, SMEM2_BYTES);
    int dev = 0, sms = NCTA;
    cudaGetDevice(&dev);
    cudaDeviceGetAttribute(&sms, cudaDevAttrMultiProcessorCount, dev);
    grid = sms < NCTA ? sms : NCTA;
    for (int i = 0; i < 10; i++) cached[i] = d_in[i];
    init = true;
  }
  attn_kernel<<<grid, 384, SMEM_BYTES>>>(maps);
  cudaLaunchConfig_t cfg = {};
  cfg.gridDim = dim3(N_CTA2); cfg.blockDim = dim3(384); cfg.dynamicSmemBytes = SMEM2_BYTES; cfg.stream = cudaStreamPerThread;
  cudaLaunchAttribute at[1];
  at[0].id = cudaLaunchAttributeProgrammaticStreamSerialization; at[0].val.programmaticStreamSerializationAllowed = PDL;
  cfg.attrs = at; cfg.numAttrs = 1;
  cudaLaunchKernelEx(&cfg, oproj_kernel, maps, (__nv_bfloat16*)d_out);
}
```

```cpp
#include <cuda_runtime.h>
#include <cuda_bf16.h>
#include <cuda.h>
#include <stdint.h>

namespace {

constexpr int NB = 8, SQ = 96, DM = 640, NH = 32, SK = 512, DH = 192;
constexpr int SLOT = 24576;
constexpr int NSLOT = 8;
constexpr int SMEM_BYTES = NSLOT * SLOT + SLOT   + 1024   + 256  ;

#define NCTA 132
#define N_ATT 66
#define NPAIR 208
#define FETCH_AHEAD 3
#define KV_INFLIGHT 8
#define WQ_EF 0
#define N_OD 20
#define PDL 1
constexpr int N_TICKETS = NPAIR + 2 * (256 - NPAIR) + (NCTA - N_ATT) / 2;

struct Maps { CUtensorMap x[2], x1[2], wq[2], k[2], v[2], wo[2]; uint32_t otab[140]; };

__device__ uint4 g_stash[2 * NH * NB * 2304];
__device__ float4 g_part[2][40 * 2 * 24 * 128];
__device__ unsigned int g_epoch;
__device__ unsigned int g_tile_cnt[40];
__device__ unsigned int g_flag[2 * NB * NH];
__device__ unsigned int g_ticket, g_done, g_done2;

#define STAMP(i, tk)

__device__ __forceinline__ uint32_t smem_u32(const void* p) { return (uint32_t)__cvta_generic_to_shared(p); }
__device__ __forceinline__ void mbar_init(uint32_t bar, int cnt) { asm volatile("mbarrier.init.shared::cta.b64 [%0], %1;" :: "r"(bar), "r"(cnt) : "memory"); }
__device__ __forceinline__ void mbar_expect_tx(uint32_t bar, uint32_t bytes) { asm volatile("mbarrier.arrive.expect_tx.shared::cta.b64 _, [%0], %1;" :: "r"(bar), "r"(bytes) : "memory"); }
__device__ __forceinline__ void mbar_arrive(uint32_t bar) { asm volatile("mbarrier.arrive.shared::cta.b64 _, [%0];" :: "r"(bar) : "memory"); }
__device__ __forceinline__ void mbar_wait(uint32_t bar, uint32_t parity) {
  asm volatile("{\n.reg .pred p;\nWAIT_%=:\nmbarrier.try_wait.parity.shared::cta.b64 p, [%0], %1;\n@p bra DONE_%=;\nbra WAIT_%=;\nDONE_%=:\n}" :: "r"(bar), "r"(parity) : "memory");
}
__device__ __forceinline__ void tma_2d(uint32_t dst, const CUtensorMap* m, int c0, int c1, uint32_t bar) {
  asm volatile("cp.async.bulk.tensor.2d.shared::cluster.global.mbarrier::complete_tx::bytes [%0], [%1, {%3, %4}], [%2];"
               :: "r"(dst), "l"(m), "r"(bar), "r"(c0), "r"(c1) : "memory");
}
__device__ __forceinline__ void tma_3d(uint32_t dst, const CUtensorMap* m, int c0, int c1, int c2, uint32_t bar) {
  asm volatile("cp.async.bulk.tensor.3d.shared::cluster.global.mbarrier::complete_tx::bytes [%0], [%1, {%3, %4, %5}], [%2];"
               :: "r"(dst), "l"(m), "r"(bar), "r"(c0), "r"(c1), "r"(c2) : "memory");
}
__device__ __forceinline__ void tma_4d(uint32_t dst, const CUtensorMap* m, int c2, int c3, uint32_t bar) {
  asm volatile("cp.async.bulk.tensor.4d.shared::cluster.global.mbarrier::complete_tx::bytes [%0], [%1, {%3, %3, %4, %5}], [%2];"
               :: "r"(dst), "l"(m), "r"(bar), "r"(0), "r"(c2), "r"(c3) : "memory");
}
__device__ __forceinline__ void tma_4d_hint(uint32_t dst, const CUtensorMap* m, int c2, int c3, uint32_t bar, uint64_t pol) {
  asm volatile("cp.async.bulk.tensor.4d.shared::cluster.global.mbarrier::complete_tx::bytes.L2::cache_hint [%0], [%1, {%3, %3, %4, %5}], [%2], %6;"
               :: "r"(dst), "l"(m), "r"(bar), "r"(0), "r"(c2), "r"(c3), "l"(pol) : "memory");
}
__device__ __forceinline__ void bulk_load(uint32_t dst, const void* src, uint32_t bytes, uint32_t bar) {
  asm volatile("cp.async.bulk.shared::cluster.global.mbarrier::complete_tx::bytes [%0], [%1], %2, [%3];" :: "r"(dst), "l"(src), "r"(bytes), "r"(bar) : "memory");
}
__device__ __forceinline__ void wg_fence() { asm volatile("wgmma.fence.sync.aligned;" ::: "memory"); }
__device__ __forceinline__ void wg_commit() { asm volatile("wgmma.commit_group.sync.aligned;" ::: "memory"); }
template <int N> __device__ __forceinline__ void wg_wait() { asm volatile("wgmma.wait_group.sync.aligned %0;" :: "n"(N) : "memory"); }
template <int N> __device__ __forceinline__ void touch(float (&d)[N]) {
#pragma unroll
  for (int i = 0; i < N; i++) asm volatile("" : "+f"(d[i]) :: "memory");
}
template <int N> __device__ __forceinline__ void touch_u(uint32_t (&d)[N]) {
#pragma unroll
  for (int i = 0; i < N; i++) asm volatile("" : "+r"(d[i]) :: "memory");
}
__device__ __forceinline__ float ex2(float x) { float y; asm("ex2.approx.ftz.f32 %0, %1;" : "=f"(y) : "f"(x)); return y; }
__device__ __forceinline__ uint32_t pack_bf16(float lo, float hi) { uint32_t r; asm("cvt.rn.bf16x2.f32 %0, %1, %2;" : "=r"(r) : "f"(hi), "f"(lo)); return r; }

constexpr uint64_t DESC_SW128 = (uint64_t)1 << 62;
__device__ __forceinline__ uint64_t desc_kmajor_sw128(uint32_t addr) {
  return DESC_SW128 | ((uint64_t)(1024 >> 4) << 32) | ((uint64_t)1 << 16) | (uint64_t)((addr & 0x3FFFF) >> 4);
}
__device__ __forceinline__ uint64_t desc_k_il(uint32_t addr) {
  return DESC_SW128 | ((uint64_t)(3072 >> 4) << 32) | ((uint64_t)1 << 16) | (uint64_t)((addr & 0x3FFFF) >> 4);
}
__device__ __forceinline__ uint64_t desc_mn_il(uint32_t addr) {
  return DESC_SW128 | ((uint64_t)(3072 >> 4) << 32) | ((uint64_t)(1024 >> 4) << 16) | (uint64_t)((addr & 0x3FFFF) >> 4);
}
template <int LBO> __device__ __forceinline__ uint64_t desc_mnmajor_sw128(uint32_t addr) {
  return DESC_SW128 | ((uint64_t)(1024 >> 4) << 32) | ((uint64_t)(LBO >> 4) << 16) | (uint64_t)((addr & 0x3FFFF) >> 4);
}
__device__ __forceinline__ uint64_t desc_kmajor_nosw(uint32_t addr) {
  return ((uint64_t)(1024 >> 4) << 32) | ((uint64_t)(128 >> 4) << 16) | (uint64_t)((addr & 0x3FFFF) >> 4);
}

__device__ __forceinline__ void wgmma_rs_n64_t0(float (&d)[32], uint32_t a0, uint32_t a1, uint32_t a2, uint32_t a3, uint64_t descB, int scaleD) {
  asm volatile("{\n.reg .pred p;\nsetp.ne.b32 p, %37, 0;\n"
    "wgmma.mma_async.sync.aligned.m64n64k16.f32.bf16.bf16 "
    "{%0, %1, %2, %3, %4, %5, %6, %7, %8, %9, %10, %11, %12, %13, %14, %15, %16, %17, %18, %19, %20, %21, %22, %23, %24, %25, %26, %27, %28, %29, %30, %31}, "
    "{%32, %33, %34, %35}, %36, p, 1, 1, 0;\n}\n"
    : "+f"(d[0]), "+f"(d[1]), "+f"(d[2]), "+f"(d[3]), "+f"(d[4]), "+f"(d[5]), "+f"(d[6]), "+f"(d[7]), "+f"(d[8]), "+f"(d[9]), "+f"(d[10]), "+f"(d[11]), "+f"(d[12]), "+f"(d[13]), "+f"(d[14]), "+f"(d[15]), "+f"(d[16]), "+f"(d[17]), "+f"(d[18]), "+f"(d[19]), "+f"(d[20]), "+f"(d[21]), "+f"(d[22]), "+f"(d[23]), "+f"(d[24]), "+f"(d[25]), "+f"(d[26]), "+f"(d[27]), "+f"(d[28]), "+f"(d[29]), "+f"(d[30]), "+f"(d[31])
    : "r"(a0), "r"(a1), "r"(a2), "r"(a3), "l"(descB), "r"(scaleD));
}
__device__ __forceinline__ void wgmma_rs_n192_t1(float (&d)[96], uint32_t a0, uint32_t a1, uint32_t a2, uint32_t a3, uint64_t descB, int scaleD) {
  asm volatile("{\n.reg .pred p;\nsetp.ne.b32 p, %101, 0;\n"
    "wgmma.mma_async.sync.aligned.m64n192k16.f32.bf16.bf16 "
    "{%0, %1, %2, %3, %4, %5, %6, %7, %8, %9, %10, %11, %12, %13, %14, %15, %16, %17, %18, %19, %20, %21, %22, %23, %24, %25, %26, %27, %28, %29, %30, %31, %32, %33, %34, %35, %36, %37, %38, %39, %40, %41, %42, %43, %44, %45, %46, %47, %48, %49, %50, %51, %52, %53, %54, %55, %56, %57, %58, %59, %60, %61, %62, %63, %64, %65, %66, %67, %68, %69, %70, %71, %72, %73, %74, %75, %76, %77, %78, %79, %80, %81, %82, %83, %84, %85, %86, %87, %88, %89, %90, %91, %92, %93, %94, %95}, "
    "{%96, %97, %98, %99}, %100, p, 1, 1, 1;\n}\n"
    : "+f"(d[0]), "+f"(d[1]), "+f"(d[2]), "+f"(d[3]), "+f"(d[4]), "+f"(d[5]), "+f"(d[6]), "+f"(d[7]), "+f"(d[8]), "+f"(d[9]), "+f"(d[10]), "+f"(d[11]), "+f"(d[12]), "+f"(d[13]), "+f"(d[14]), "+f"(d[15]), "+f"(d[16]), "+f"(d[17]), "+f"(d[18]), "+f"(d[19]), "+f"(d[20]), "+f"(d[21]), "+f"(d[22]), "+f"(d[23]), "+f"(d[24]), "+f"(d[25]), "+f"(d[26]), "+f"(d[27]), "+f"(d[28]), "+f"(d[29]), "+f"(d[30]), "+f"(d[31]), "+f"(d[32]), "+f"(d[33]), "+f"(d[34]), "+f"(d[35]), "+f"(d[36]), "+f"(d[37]), "+f"(d[38]), "+f"(d[39]), "+f"(d[40]), "+f"(d[41]), "+f"(d[42]), "+f"(d[43]), "+f"(d[44]), "+f"(d[45]), "+f"(d[46]), "+f"(d[47]), "+f"(d[48]), "+f"(d[49]), "+f"(d[50]), "+f"(d[51]), "+f"(d[52]), "+f"(d[53]), "+f"(d[54]), "+f"(d[55]), "+f"(d[56]), "+f"(d[57]), "+f"(d[58]), "+f"(d[59]), "+f"(d[60]), "+f"(d[61]), "+f"(d[62]), "+f"(d[63]), "+f"(d[64]), "+f"(d[65]), "+f"(d[66]), "+f"(d[67]), "+f"(d[68]), "+f"(d[69]), "+f"(d[70]), "+f"(d[71]), "+f"(d[72]), "+f"(d[73]), "+f"(d[74]), "+f"(d[75]), "+f"(d[76]), "+f"(d[77]), "+f"(d[78]), "+f"(d[79]), "+f"(d[80]), "+f"(d[81]), "+f"(d[82]), "+f"(d[83]), "+f"(d[84]), "+f"(d[85]), "+f"(d[86]), "+f"(d[87]), "+f"(d[88]), "+f"(d[89]), "+f"(d[90]), "+f"(d[91]), "+f"(d[92]), "+f"(d[93]), "+f"(d[94]), "+f"(d[95])
    : "r"(a0), "r"(a1), "r"(a2), "r"(a3), "l"(descB), "r"(scaleD));
}
__device__ __forceinline__ void wgmma_ss_n192_t1(float (&d)[96], uint64_t descA, uint64_t descB, int scaleD) {
  asm volatile("{\n.reg .pred p;\nsetp.ne.b32 p, %98, 0;\n"
    "wgmma.mma_async.sync.aligned.m64n192k16.f32.bf16.bf16 "
    "{%0, %1, %2, %3, %4, %5, %6, %7, %8, %9, %10, %11, %12, %13, %14, %15, %16, %17, %18, %19, %20, %21, %22, %23, %24, %25, %26, %27, %28, %29, %30, %31, %32, %33, %34, %35, %36, %37, %38, %39, %40, %41, %42, %43, %44, %45, %46, %47, %48, %49, %50, %51, %52, %53, %54, %55, %56, %57, %58, %59, %60, %61, %62, %63, %64, %65, %66, %67, %68, %69, %70, %71, %72, %73, %74, %75, %76, %77, %78, %79, %80, %81, %82, %83, %84, %85, %86, %87, %88, %89, %90, %91, %92, %93, %94, %95}, "
    "%96, %97, p, 1, 1, 0, 1;\n}\n"
    : "+f"(d[0]), "+f"(d[1]), "+f"(d[2]), "+f"(d[3]), "+f"(d[4]), "+f"(d[5]), "+f"(d[6]), "+f"(d[7]), "+f"(d[8]), "+f"(d[9]), "+f"(d[10]), "+f"(d[11]), "+f"(d[12]), "+f"(d[13]), "+f"(d[14]), "+f"(d[15]), "+f"(d[16]), "+f"(d[17]), "+f"(d[18]), "+f"(d[19]), "+f"(d[20]), "+f"(d[21]), "+f"(d[22]), "+f"(d[23]), "+f"(d[24]), "+f"(d[25]), "+f"(d[26]), "+f"(d[27]), "+f"(d[28]), "+f"(d[29]), "+f"(d[30]), "+f"(d[31]), "+f"(d[32]), "+f"(d[33]), "+f"(d[34]), "+f"(d[35]), "+f"(d[36]), "+f"(d[37]), "+f"(d[38]), "+f"(d[39]), "+f"(d[40]), "+f"(d[41]), "+f"(d[42]), "+f"(d[43]), "+f"(d[44]), "+f"(d[45]), "+f"(d[46]), "+f"(d[47]), "+f"(d[48]), "+f"(d[49]), "+f"(d[50]), "+f"(d[51]), "+f"(d[52]), "+f"(d[53]), "+f"(d[54]), "+f"(d[55]), "+f"(d[56]), "+f"(d[57]), "+f"(d[58]), "+f"(d[59]), "+f"(d[60]), "+f"(d[61]), "+f"(d[62]), "+f"(d[63]), "+f"(d[64]), "+f"(d[65]), "+f"(d[66]), "+f"(d[67]), "+f"(d[68]), "+f"(d[69]), "+f"(d[70]), "+f"(d[71]), "+f"(d[72]), "+f"(d[73]), "+f"(d[74]), "+f"(d[75]), "+f"(d[76]), "+f"(d[77]), "+f"(d[78]), "+f"(d[79]), "+f"(d[80]), "+f"(d[81]), "+f"(d[82]), "+f"(d[83]), "+f"(d[84]), "+f"(d[85]), "+f"(d[86]), "+f"(d[87]), "+f"(d[88]), "+f"(d[89]), "+f"(d[90]), "+f"(d[91]), "+f"(d[92]), "+f"(d[93]), "+f"(d[94]), "+f"(d[95])
    : "l"(descA), "l"(descB), "r"(scaleD));
}
__device__ __forceinline__ void wgmma_ss_n64_t1(float (&d)[32], uint64_t descA, uint64_t descB, int scaleD) {
  asm volatile("{\n.reg .pred p;\nsetp.ne.b32 p, %34, 0;\n"
    "wgmma.mma_async.sync.aligned.m64n64k16.f32.bf16.bf16 "
    "{%0, %1, %2, %3, %4, %5, %6, %7, %8, %9, %10, %11, %12, %13, %14, %15, %16, %17, %18, %19, %20, %21, %22, %23, %24, %25, %26, %27, %28, %29, %30, %31}, "
    "%32, %33, p, 1, 1, 0, 1;\n}\n"
    : "+f"(d[0]), "+f"(d[1]), "+f"(d[2]), "+f"(d[3]), "+f"(d[4]), "+f"(d[5]), "+f"(d[6]), "+f"(d[7]), "+f"(d[8]), "+f"(d[9]), "+f"(d[10]), "+f"(d[11]), "+f"(d[12]), "+f"(d[13]), "+f"(d[14]), "+f"(d[15]), "+f"(d[16]), "+f"(d[17]), "+f"(d[18]), "+f"(d[19]), "+f"(d[20]), "+f"(d[21]), "+f"(d[22]), "+f"(d[23]), "+f"(d[24]), "+f"(d[25]), "+f"(d[26]), "+f"(d[27]), "+f"(d[28]), "+f"(d[29]), "+f"(d[30]), "+f"(d[31])
    : "l"(descA), "l"(descB), "r"(scaleD));
}
__device__ __forceinline__ void wgmma_ss_n32_t1(float (&d)[16], uint64_t descA, uint64_t descB, int scaleD) {
  asm volatile("{\n.reg .pred p;\nsetp.ne.b32 p, %18, 0;\n"
    "wgmma.mma_async.sync.aligned.m64n32k16.f32.bf16.bf16 "
    "{%0, %1, %2, %3, %4, %5, %6, %7, %8, %9, %10, %11, %12, %13, %14, %15}, "
    "%16, %17, p, 1, 1, 0, 1;\n}\n"
    : "+f"(d[0]), "+f"(d[1]), "+f"(d[2]), "+f"(d[3]), "+f"(d[4]), "+f"(d[5]), "+f"(d[6]), "+f"(d[7]), "+f"(d[8]), "+f"(d[9]), "+f"(d[10]), "+f"(d[11]), "+f"(d[12]), "+f"(d[13]), "+f"(d[14]), "+f"(d[15])
    : "l"(descA), "l"(descB), "r"(scaleD));
}
__device__ __forceinline__ void wgmma_st_n192_t0(float (&d)[96], uint64_t descA, uint64_t descB, int scaleD) {
  asm volatile("{\n.reg .pred p;\nsetp.ne.b32 p, %98, 0;\n"
    "wgmma.mma_async.sync.aligned.m64n192k16.f32.bf16.bf16 "
    "{%0, %1, %2, %3, %4, %5, %6, %7, %8, %9, %10, %11, %12, %13, %14, %15, %16, %17, %18, %19, %20, %21, %22, %23, %24, %25, %26, %27, %28, %29, %30, %31, %32, %33, %34, %35, %36, %37, %38, %39, %40, %41, %42, %43, %44, %45, %46, %47, %48, %49, %50, %51, %52, %53, %54, %55, %56, %57, %58, %59, %60, %61, %62, %63, %64, %65, %66, %67, %68, %69, %70, %71, %72, %73, %74, %75, %76, %77, %78, %79, %80, %81, %82, %83, %84, %85, %86, %87, %88, %89, %90, %91, %92, %93, %94, %95}, "
    "%96, %97, p, 1, 1, 1, 0;\n}\n"
    : "+f"(d[0]), "+f"(d[1]), "+f"(d[2]), "+f"(d[3]), "+f"(d[4]), "+f"(d[5]), "+f"(d[6]), "+f"(d[7]), "+f"(d[8]), "+f"(d[9]), "+f"(d[10]), "+f"(d[11]), "+f"(d[12]), "+f"(d[13]), "+f"(d[14]), "+f"(d[15]), "+f"(d[16]), "+f"(d[17]), "+f"(d[18]), "+f"(d[19]), "+f"(d[20]), "+f"(d[21]), "+f"(d[22]), "+f"(d[23]), "+f"(d[24]), "+f"(d[25]), "+f"(d[26]), "+f"(d[27]), "+f"(d[28]), "+f"(d[29]), "+f"(d[30]), "+f"(d[31]), "+f"(d[32]), "+f"(d[33]), "+f"(d[34]), "+f"(d[35]), "+f"(d[36]), "+f"(d[37]), "+f"(d[38]), "+f"(d[39]), "+f"(d[40]), "+f"(d[41]), "+f"(d[42]), "+f"(d[43]), "+f"(d[44]), "+f"(d[45]), "+f"(d[46]), "+f"(d[47]), "+f"(d[48]), "+f"(d[49]), "+f"(d[50]), "+f"(d[51]), "+f"(d[52]), "+f"(d[53]), "+f"(d[54]), "+f"(d[55]), "+f"(d[56]), "+f"(d[57]), "+f"(d[58]), "+f"(d[59]), "+f"(d[60]), "+f"(d[61]), "+f"(d[62]), "+f"(d[63]), "+f"(d[64]), "+f"(d[65]), "+f"(d[66]), "+f"(d[67]), "+f"(d[68]), "+f"(d[69]), "+f"(d[70]), "+f"(d[71]), "+f"(d[72]), "+f"(d[73]), "+f"(d[74]), "+f"(d[75]), "+f"(d[76]), "+f"(d[77]), "+f"(d[78]), "+f"(d[79]), "+f"(d[80]), "+f"(d[81]), "+f"(d[82]), "+f"(d[83]), "+f"(d[84]), "+f"(d[85]), "+f"(d[86]), "+f"(d[87]), "+f"(d[88]), "+f"(d[89]), "+f"(d[90]), "+f"(d[91]), "+f"(d[92]), "+f"(d[93]), "+f"(d[94]), "+f"(d[95])
    : "l"(descA), "l"(descB), "r"(scaleD));
}

__device__ __forceinline__ unsigned int ld_acquire(const unsigned int* p) { unsigned int v; asm volatile("ld.acquire.gpu.global.u32 %0, [%1];" : "=r"(v) : "l"(p) : "memory"); return v; }

struct Cons {
  uint32_t base, full0;
  uint32_t it;
  int lane;
  __device__ __forceinline__ uint32_t wait(uint32_t slot, uint32_t u) const { mbar_wait(full0 + slot * 8, (u >> 3) & 1); return base + slot * SLOT; }
  __device__ __forceinline__ uint32_t wait(uint32_t u) const { return wait(u & 7, u); }
  __device__ __forceinline__ void release(uint32_t slot) const { if (lane == 0) mbar_arrive(full0 + 64 + (slot & 7) * 8); }
};

__device__ __forceinline__ int ticket_task(int ticket) {
  int u = ticket, f = 0;
  if (ticket >= N_ATT) {
    if (ticket < NCTA) { const int s = ticket - N_ATT; u = N_ATT + (s >> 1); f = 1 | ((s & 1) << 2); }
    else {
      u = ticket - (NCTA - N_ATT) / 2;
      if (u >= NPAIR) { const int s = u - NPAIR; u = NPAIR + (s >> 1); f = 1 | ((s & 1) << 2); }
    }
  }
  const int hh = u & 7, pr = (u >> 3) & 3, g = (u >> 5) & 3, blk = u >> 7;
  return f | (pr << 3) | ((g * 8 + hh) << 5) | (blk << 10);
}

__device__ __forceinline__ void qproj(Cons& r, uint32_t (&qf)[48], uint32_t park, bool pair, int wg, int tid) {
  float acc[96];
  float acx[32];
  float acy[16];
  for (int c = 0; c < 10; c++) {
    const uint32_t sx = r.it;
    const uint32_t xa = r.wait(sx), wa = r.wait(sx + 1);
    const uint64_t da = desc_kmajor_sw128(xa + wg * 8192), d2 = desc_kmajor_sw128(xa + 2 * 8192);
    const uint64_t db = desc_mn_il(wa), dbx = desc_mn_il(wa + wg * 1024), dby = desc_mn_il(wa + 2048 + wg * 64);
    if (pair) {
      wg_fence();
#pragma unroll
      for (int ks = 0; ks < 4; ks++) {
        const int sc = (c > 0 || ks > 0) ? 1 : 0;
        wgmma_ss_n192_t1(acc, da + ks * 2, db + ks * 384, sc);
        wgmma_ss_n64_t1(acx, d2 + ks * 2, dbx + ks * 384, sc);
        wgmma_ss_n32_t1(acy, d2 + ks * 2, dby + ks * 384, sc);
      }
      wg_commit();
    } else {
      wg_fence();
#pragma unroll
      for (int ks = 0; ks < 4; ks++)
        wgmma_ss_n192_t1(acc, da + ks * 2, db + ks * 384, (c > 0 || ks > 0) ? 1 : 0);
      wg_commit();
    }
    if (c > 0) { wg_wait<1>(); r.release((sx + 6) & 7); r.release((sx + 7) & 7); }
    r.it += 2;
  }
  wg_wait<0>();
  touch(acc); touch(acx); touch(acy);
  r.release((r.it + 6) & 7); r.release((r.it + 7) & 7);
  if (pair) {
#pragma unroll
    for (int ks = 0; ks < 4; ks++) {
      uint32_t a0 = pack_bf16(acx[8 * ks + 0], acx[8 * ks + 1]), a1 = pack_bf16(acx[8 * ks + 2], acx[8 * ks + 3]);
      uint32_t a2 = pack_bf16(acx[8 * ks + 4], acx[8 * ks + 5]), a3 = pack_bf16(acx[8 * ks + 6], acx[8 * ks + 7]);
      asm volatile("st.shared.v4.b32 [%0], {%1, %2, %3, %4};" :: "r"(park + ((wg * 4 + ks) * 128 + tid) * 16), "r"(a0), "r"(a1), "r"(a2), "r"(a3) : "memory");
    }
#pragma unroll
    for (int ks = 0; ks < 2; ks++) {
      uint32_t a0 = pack_bf16(acy[8 * ks + 0], acy[8 * ks + 1]), a1 = pack_bf16(acy[8 * ks + 2], acy[8 * ks + 3]);
      uint32_t a2 = pack_bf16(acy[8 * ks + 4], acy[8 * ks + 5]), a3 = pack_bf16(acy[8 * ks + 6], acy[8 * ks + 7]);
      asm volatile("st.shared.v4.b32 [%0], {%1, %2, %3, %4};" :: "r"(park + ((8 + wg * 2 + ks) * 128 + tid) * 16), "r"(a0), "r"(a1), "r"(a2), "r"(a3) : "memory");
    }
  }
#pragma unroll
  for (int i = 0; i < 48; i++) qf[i] = pack_bf16(acc[2 * i], acc[2 * i + 1]);
}

__device__ __forceinline__ void sched_sync(int wg) { asm volatile("bar.sync %0, 256;" :: "r"(2 + wg) : "memory"); }
__device__ __forceinline__ void sched_arrive(int wg) { asm volatile("bar.arrive %0, 256;" :: "r"(3 - wg) : "memory"); }

__device__ __forceinline__ void issue_qk(float (&s)[32], const uint32_t (&qf)[48], uint64_t dk) {
#pragma unroll
  for (int ks = 0; ks < 12; ks++)
    wgmma_rs_n64_t0(s, qf[4 * ks], qf[4 * ks + 1], qf[4 * ks + 2], qf[4 * ks + 3], dk + ((ks >> 2) * 64 + (ks & 3) * 2), ks > 0);
  wg_commit();
}
__device__ __forceinline__ void attention(Cons& r, const uint32_t (&qf)[48], bool valid, uint32_t* dst, uint32_t sig, int wg) {
  constexpr float CS = 0.07216878364870322f * 1.4426950408889634f;
  const int lane = r.lane;
  float o[96];
  float s[32];
  uint32_t pa[8], pb[8];
  float m0 = -INFINITY, m1 = -INFINITY, l0 = 0.f, l1 = 0.f, al0 = 1.f, al1 = 1.f;
  bool resc = false;
#pragma unroll
  for (int i = 0; i < 8; i++) { pa[i] = 0; pb[i] = 0; }

  auto row_max = [&]() {
    float x0 = fmaxf(s[0], s[1]), x1 = fmaxf(s[2], s[3]), y0 = fmaxf(s[4], s[5]), y1 = fmaxf(s[6], s[7]);
#pragma unroll
    for (int i = 2; i < 8; i += 2) {
      x0 = fmaxf(x0, fmaxf(s[4 * i], s[4 * i + 1])); x1 = fmaxf(x1, fmaxf(s[4 * i + 2], s[4 * i + 3]));
      y0 = fmaxf(y0, fmaxf(s[4 * i + 4], s[4 * i + 5])); y1 = fmaxf(y1, fmaxf(s[4 * i + 6], s[4 * i + 7]));
    }
    x0 = fmaxf(x0, y0); x1 = fmaxf(x1, y1);
    x0 = fmaxf(x0, __shfl_xor_sync(0xffffffffu, x0, 1)); x1 = fmaxf(x1, __shfl_xor_sync(0xffffffffu, x1, 1));
    x0 = fmaxf(x0, __shfl_xor_sync(0xffffffffu, x0, 2)); x1 = fmaxf(x1, __shfl_xor_sync(0xffffffffu, x1, 2));
    resc = __any_sync(0xffffffffu, (x0 - m0) * CS > 8.0f || (x1 - m1) * CS > 8.0f);
    if (resc) {
      const float n0 = fmaxf(m0, x0), n1 = fmaxf(m1, x1);
      al0 = ex2((m0 - n0) * CS); al1 = ex2((m1 - n1) * CS);
      m0 = n0; m1 = n1;
      l0 *= al0; l1 *= al1;
    }
  };
  auto exps = [&](uint32_t (&p)[8], int h) {
    const float c0 = m0 * CS, c1 = m1 * CS;
    float t0 = 0.f, t1 = 0.f;
#pragma unroll
    for (int i = 0; i < 4; i++) {
      const int k = 16 * h + 4 * i;
      const float e0 = ex2(fmaf(s[k], CS, -c0)), e1 = ex2(fmaf(s[k + 1], CS, -c0));
      const float e2 = ex2(fmaf(s[k + 2], CS, -c1)), e3 = ex2(fmaf(s[k + 3], CS, -c1));
      t0 += e0 + e1; t1 += e2 + e3;
      p[2 * i] = pack_bf16(e0, e1); p[2 * i + 1] = pack_bf16(e2, e3);
    }
    l0 += t0; l1 += t1;
  };
  auto pv_a = [&](uint64_t dv, int first) {
    wgmma_rs_n192_t1(o, pa[0], pa[1], pa[2], pa[3], dv, first ? 0 : 1);
    wgmma_rs_n192_t1(o, pa[4], pa[5], pa[6], pa[7], dv + 384, 1);
    wg_commit();
  };
  auto pv_b = [&](uint64_t dv) {
    wgmma_rs_n192_t1(o, pb[0], pb[1], pb[2], pb[3], dv + 768, 1);
    wgmma_rs_n192_t1(o, pb[4], pb[5], pb[6], pb[7], dv + 1152, 1);
    wg_commit();
  };

  if (wg == 1) sched_arrive(1);
  {
    const uint32_t sk = r.it & 7;
    const uint64_t dk = desc_k_il(r.wait(sk, r.it));
    sched_sync(wg);
    wg_fence();
    issue_qk(s, qf, dk);
    sched_arrive(wg);
    wg_wait<0>();
    touch(s);
    r.release(sk);
    if (valid) { row_max(); exps(pa, 0); exps(pb, 1); }
  }
  for (int j = 0; j < 7; j++) {
    const uint32_t u = r.it;
    const uint32_t sv = (u + 1) & 7, sk = (u + 2) & 7;
    const uint64_t dk = desc_k_il(r.wait(sk, u + 2));
    const uint64_t dv = desc_mn_il(r.wait(sv, u + 1));
    sched_sync(wg);
    wg_fence();
    issue_qk(s, qf, dk);
    pv_a(dv, j == 0);
    pv_b(dv);
    sched_arrive(wg);
    wg_wait<2>();
    touch(s);
    r.release(sk);
    if (valid) row_max();
    wg_wait<1>();
    touch_u(pa);
    if (valid) exps(pa, 0);
    touch_u(pa);
    wg_wait<0>();
    touch(o); touch_u(pb);
    r.release(sv);
    if (valid) exps(pb, 1);
    if (resc) {
#pragma unroll
      for (int i = 0; i < 24; i++) { o[4 * i] *= al0; o[4 * i + 1] *= al0; o[4 * i + 2] *= al1; o[4 * i + 3] *= al1; }
    }
    touch_u(pb);
    r.it += 2;
  }
  {
    const uint32_t sv = (r.it + 1) & 7;
    const uint64_t dv = desc_mn_il(r.wait(sv, r.it + 1));
    sched_sync(wg);
    wg_fence();
    pv_a(dv, 0);
    pv_b(dv);
    if (wg == 0) sched_arrive(0);
    wg_wait<0>();
    touch(o); touch_u(pa); touch_u(pb);
    r.release(sv);
    r.it += 2;
  }
  if (valid) {
    l0 += __shfl_xor_sync(0xffffffffu, l0, 1); l1 += __shfl_xor_sync(0xffffffffu, l1, 1);
    l0 += __shfl_xor_sync(0xffffffffu, l0, 2); l1 += __shfl_xor_sync(0xffffffffu, l1, 2);
    const float i0 = 1.0f / l0, i1 = 1.0f / l1;
#pragma unroll
    for (int kc = 0; kc < 24; kc++) {
      dst[(kc >> 3) * 3072 + (kc & 7) * 32 + lane] = pack_bf16(o[4 * kc] * i0, o[4 * kc + 1] * i0);
      dst[(kc >> 3) * 3072 + 256 + (kc & 7) * 32 + lane] = pack_bf16(o[4 * kc + 2] * i1, o[4 * kc + 3] * i1);
    }
    __syncwarp();
    if (lane == 0) mbar_arrive(sig);
  }
}

__global__ void __launch_bounds__(384, 1) attn_kernel(const __grid_constant__ Maps maps) {
  extern __shared__ uint8_t smem_raw[];
  const uint32_t sbase = (smem_u32(smem_raw) + 1023u) & ~1023u;
  const uint32_t park = sbase + NSLOT * SLOT;
  const uint32_t bars = park + SLOT;
  const uint32_t full0 = bars, empty0 = bars + 64;
  const uint32_t tfull0 = bars + 128, tempty0 = bars + 160, sig0 = bars + 192, tbox = bars + 224, sreq = bars + 240;
  const int warp = __shfl_sync(0xffffffffu, threadIdx.x >> 5, 0), lane = threadIdx.x & 31;
  if (threadIdx.x == 0) {
    for (int i = 0; i < NSLOT; i++) { mbar_init(full0 + 8 * i, 1); mbar_init(empty0 + 8 * i, 8); }
    for (int i = 0; i < 4; i++) { mbar_init(tfull0 + 8 * i, 1); mbar_init(tempty0 + 8 * i, 10); mbar_init(sig0 + 8 * i, 6); }
    mbar_init(sreq, 1);
    asm volatile("fence.mbarrier_init.release.cluster;" ::: "memory");
  }
  __syncthreads();
  asm volatile("griddepcontrol.launch_dependents;");

  if (warp < 4) {
    asm volatile("setmaxnreg.dec.sync.aligned.u32 24;");
    if (warp == 0 && lane == 0) {
      uint64_t pol; asm volatile("createpolicy.fractional.L2::evict_first.b64 %0, 1.0;" : "=l"(pol));
      uint32_t u = 0;
      auto acquire = [&](uint32_t bytes) -> uint32_t {
        const uint32_t s = u & 7;
        mbar_wait(empty0 + 8 * s, ((u >> 3) & 1) ^ 1);
        mbar_expect_tx(full0 + 8 * s, bytes);
        u++;
        return s;
      };
      for (uint32_t n = 0;; n++) {
        int task;
        mbar_wait(tfull0 + 8 * (n & 3), (n >> 2) & 1);
        asm volatile("ld.shared.b32 %0, [%1];" : "=r"(task) : "r"(tbox + 4 * (n & 3)) : "memory");
        mbar_arrive(tempty0 + 8 * (n & 3));
        if (task < 0) break;
        const int type = task & 3, bsel = (task >> 2) & 1, pr = (task >> 3) & 3, h = (task >> 5) & 31, blk = (task >> 10) & 1;
        if (type != 2) {
          const CUtensorMap* mx = type ? &maps.x1[blk] : &maps.x[blk];
#pragma unroll 1
          for (int c = 0; c < 10; c++) {
            uint32_t s = acquire(type ? SLOT / 2 : SLOT);
            tma_2d(sbase + s * SLOT, mx, c * 64, pr * 192 + bsel * 96, full0 + 8 * s);
            s = acquire(SLOT);
            if (WQ_EF) tma_4d_hint(sbase + s * SLOT, &maps.wq[blk], h * 3, c * 8, full0 + 8 * s, pol);
            else tma_4d(sbase + s * SLOT, &maps.wq[blk], h * 3, c * 8, full0 + 8 * s);
          }
        }
        int rg = (((pr * 2 + bsel) * NH + h) * SK) >> 3;
#pragma unroll 1
        for (int j = 0; j < 8; j++) {
          if (j == 8 - FETCH_AHEAD) mbar_arrive(sreq);
          if (KV_INFLIGHT < 8 && u >= KV_INFLIGHT) mbar_wait(full0 + 8 * ((u - KV_INFLIGHT) & 7), ((u - KV_INFLIGHT) >> 3) & 1);
          uint32_t s = acquire(SLOT);
          tma_4d_hint(sbase + s * SLOT, &maps.k[blk], 0, rg, full0 + 8 * s, pol);
          if (KV_INFLIGHT < 8 && u >= KV_INFLIGHT) mbar_wait(full0 + 8 * ((u - KV_INFLIGHT) & 7), ((u - KV_INFLIGHT) >> 3) & 1);
          s = acquire(SLOT);
          tma_4d_hint(sbase + s * SLOT, &maps.v[blk], 0, rg, full0 + 8 * s, pol);
          rg += 8;
        }
      }
    } else if (warp == 1 && lane == 0) {
      int task = ticket_task(blockIdx.x);
      for (uint32_t n = 0;; n++) {
        mbar_wait(tempty0 + 8 * (n & 3), ((n >> 2) & 1) ^ 1);
        asm volatile("st.shared.b32 [%0], %1;" :: "r"(tbox + 4 * (n & 3)), "r"(task) : "memory");
        mbar_arrive(tfull0 + 8 * (n & 3));
        if (task < 0) break;
        if ((task & 3) == 0) {
          task |= 2 | 4;
        } else {
          mbar_wait(sreq, n & 1);
          if ((int)blockIdx.x < N_OD) { task = -1; continue; }
          const unsigned int tk = atomicAdd(&g_ticket, 1u) + gridDim.x;
          task = tk < (unsigned)N_TICKETS ? ticket_task((int)tk) : -1;
          continue;
        }
        mbar_wait(sreq, n & 1);
      }
      __threadfence();
      if (atomicAdd(&g_done, 1u) == gridDim.x - 1) { g_ticket = 0; g_done = 0; }
    } else if (warp == 2 && lane == 0) {
      for (uint32_t n = 0;; n++) {
        int task;
        mbar_wait(tfull0 + 8 * (n & 3), (n >> 2) & 1);
        asm volatile("ld.shared.b32 %0, [%1];" : "=r"(task) : "r"(tbox + 4 * (n & 3)) : "memory");
        if (task < 0) break;
        mbar_wait(sig0 + 8 * (n & 3), (n >> 2) & 1);
        mbar_arrive(tempty0 + 8 * (n & 3));
        __threadfence();
        const int b = ((task >> 3) & 3) * 2 + ((task >> 2) & 1), h = (task >> 5) & 31, blk = (task >> 10) & 1;
        asm volatile("st.release.gpu.global.u32 [%0], %1;" :: "l"(&g_flag[(blk * NB + b) * NH + h]), "r"(6u) : "memory");
      }
    }
  } else {
    asm volatile("setmaxnreg.inc.sync.aligned.u32 240;");
    const int wg = (warp >> 2) - 1, w = warp & 3, tid = threadIdx.x & 127;
    Cons r; r.base = sbase; r.full0 = full0; r.it = 0; r.lane = lane;
    uint32_t qf[48];
    STAMP(0, 0);
    for (uint32_t n = 0;; n++) {
      int task;
      mbar_wait(tfull0 + 8 * (n & 3), (n >> 2) & 1);
      asm volatile("ld.shared.b32 %0, [%1];" : "=r"(task) : "r"(tbox + 4 * (n & 3)) : "memory");
      task = __shfl_sync(0xffffffffu, task, 0);
      if (lane == 0) mbar_arrive(tempty0 + 8 * (n & 3));
      if (task < 0) break;
      const int type = task & 3, bsel = (task >> 2) & 1, pr = (task >> 3) & 3, h = (task >> 5) & 31, blk = (task >> 10) & 1;
      const int b = pr * 2 + bsel;
      bool valid;
      int row8;
      if (type != 2) {
        qproj(r, qf, park, type == 0, wg, tid);
        if (wg == 1 && type == 0) asm volatile("bar.arrive 1, 256;" ::: "memory");
        valid = (wg == 0 || w < 2);
        row8 = wg * 8 + w * 2;
      } else {
        if (wg == 0) {
          asm volatile("bar.sync 1, 256;" ::: "memory");
#pragma unroll
          for (int ks = 0; ks < 12; ks++)
            asm volatile("ld.shared.v4.b32 {%0, %1, %2, %3}, [%4];" : "=r"(qf[4 * ks]), "=r"(qf[4 * ks + 1]), "=r"(qf[4 * ks + 2]), "=r"(qf[4 * ks + 3]) : "r"(park + (ks * 128 + tid) * 16) : "memory");
        }
        valid = (wg == 0 || w >= 2);
        row8 = wg == 0 ? 4 + w * 2 : (w - 2) * 2;
      }
      uint32_t* st = reinterpret_cast<uint32_t*>(g_stash) + (size_t)((blk * NH + h) * NB + b) * 9216 + row8 * 256;
      attention(r, qf, valid, st, sig0 + 8 * (n & 3), wg);
      STAMP(n + 1, task);
    }
  }
}

constexpr int NS2 = 9;
constexpr int SMEM2_BYTES = NS2 * SLOT + 1024 + 256;
constexpr int AX = N_OD - 20;
#define AE 19
#define B5 0
#define CHB4 0, 8, 16, 24, 32
#define CHB5 0, 7, 13, 19, 25, 32
constexpr int N_CTA2 = N_OD + (20 - AX) + 80 + B5;
static_assert(AX >= 0 && AX <= 20 && N_CTA2 <= 140, "bad O-projection table");

__global__ void __launch_bounds__(384, 1) oproj_kernel(const __grid_constant__ Maps maps, __nv_bfloat16* out) {
  extern __shared__ uint8_t smem_raw[];
  const uint32_t sbase = (smem_u32(smem_raw) + 1023u) & ~1023u;
  const uint32_t full0 = sbase + NS2 * SLOT, empty0 = full0 + 8 * NS2;
  const int warp = __shfl_sync(0xffffffffu, threadIdx.x >> 5, 0), lane = threadIdx.x & 31;
  const uint32_t ent = maps.otab[blockIdx.x];
  const int blk = ent & 1, tl = (ent >> 1) & 31, h0 = (ent >> 6) & 63, nh = (ent >> 12) & 63;
  const unsigned int nch = (ent >> 18) & 15;
  const bool fin = (ent >> 22) & 1;
  const int pr = tl & 3, nt = tl >> 2;
  if (threadIdx.x == 0) {
    for (int i = 0; i < NS2; i++) { mbar_init(full0 + 8 * i, 1); mbar_init(empty0 + 8 * i, 8); }
    asm volatile("st.shared.b32 [%0], %1;" :: "r"(empty0 + 8 * NS2), "r"(ld_acquire(&g_epoch) & 1u) : "memory");
    asm volatile("fence.mbarrier_init.release.cluster;" ::: "memory");
  }
  __syncthreads();
  uint32_t par;
  asm volatile("ld.shared.b32 %0, [%1];" : "=r"(par) : "r"(empty0 + 8 * NS2) : "memory");

  if (warp < 4) {
    if (warp == 0) {
      uint32_t s = 0, ph = 1;
      const uint8_t* src = reinterpret_cast<const uint8_t*>(g_stash) + (size_t)((blk * NH + h0) * NB + pr * 2) * 36864;
      const unsigned int* fl = &g_flag[(blk * NB + pr * 2 + (lane >> 4)) * NH + h0 + (lane & 15)];
      unsigned int ready = 0;
#pragma unroll 1
      for (int hh = 0; hh < nh; hh++) {
        const int krow = (h0 + hh) * DH;
#pragma unroll 1
        for (int q = 0; q < 5; q++) {
          if (q == 1 && hh == 16) ready = 0;
          if (q == 1 && !((ready >> (hh & 15)) & 1)) {
            const bool watch = (hh & 16) + (lane & 15) < nh;
            for (int spin = 0; spin < (1 << 22); spin++) {
              const unsigned int m = __ballot_sync(0xffffffffu, !watch || ld_acquire(fl + (hh & 16)) == 6u);
              ready = m & (m >> 16);
              if ((ready >> (hh & 15)) & 1) break;
              __nanosleep(32);
            }
            asm volatile("fence.proxy.async;" ::: "memory");
          }
          if (lane == 0) {
            mbar_wait(empty0 + 8 * s, ph);
            mbar_expect_tx(full0 + 8 * s, SLOT);
            const uint32_t dst = sbase + s * SLOT, bar = full0 + 8 * s;
            if (q == 0 || q == 3) {
              tma_3d(dst, &maps.wo[blk], 0, krow + (q ? 96 : 0), nt * 2, bar);
            } else {
              const int kc = q == 4 ? 2 : q - 1;
              bulk_load(dst, src + kc * 12288, 12288, bar);
              bulk_load(dst + 12288, src + 36864 + kc * 12288, 12288, bar);
            }
          }
          __syncwarp();
          if (++s == NS2) { s = 0; ph ^= 1; }
        }
        src += NB * 36864;
      }
      if (fin && lane == 0) {
        const int tile = (blk * 4 + pr) * 5 + nt;
        for (int spin = 0; spin < (1 << 22) && ld_acquire(&g_tile_cnt[tile]) != (nch - 1) * 8; spin++) __nanosleep(32);
        g_tile_cnt[tile] = 0;
        asm volatile("fence.proxy.async;" ::: "memory");
        const uint8_t* ps = reinterpret_cast<const uint8_t*>(g_part[par]) + (size_t)tile * 4 * SLOT;
#pragma unroll 1
        for (int q = 0; q < 4; q++) {
          mbar_wait(empty0 + 8 * s, ph);
          mbar_expect_tx(full0 + 8 * s, SLOT);
          bulk_load(sbase + s * SLOT, ps + q * SLOT, SLOT, full0 + 8 * s);
          if (++s == NS2) { s = 0; ph ^= 1; }
        }
      }
      __syncwarp();
      asm volatile("griddepcontrol.wait;" ::: "memory");
      unsigned int d = 0;
      if (lane == 0) d = atomicAdd(&g_done2, 1u);
      if (__shfl_sync(0xffffffffu, d, 0) == gridDim.x - 1) {
        for (int i = lane; i < 2 * NB * NH; i += 32) g_flag[i] = 0;
        if (lane == 0) { g_done2 = 0; g_epoch = par ^ 1; }
      }
    }
  } else {
    const int wg = (warp >> 2) - 1, w = warp & 3, tid = threadIdx.x & 127;
    uint32_t s = 0, ph = 0;
    auto next = [&](uint32_t& slot) -> uint32_t {
      slot = s;
      mbar_wait(full0 + 8 * s, ph);
      if (++s == NS2) { s = 0; ph ^= 1; }
      return sbase + slot * SLOT;
    };
    auto release = [&](uint32_t slot) { if (lane == 0) mbar_arrive(empty0 + 8 * slot); };
    const int tile = (blk * 4 + pr) * 5 + nt;
    float acc[96];
    uint32_t pw1 = 0, po2 = 0;
    for (int hh = 0; hh < nh; hh++) {
      uint32_t sw0, so0, so1, sw1, so2;
      const uint64_t dw0 = desc_mnmajor_sw128<1024>(next(sw0) + wg * 12288);
      const uint64_t do0 = desc_kmajor_nosw(next(so0));
      wg_fence();
#pragma unroll
      for (int ks = 0; ks < 4; ks++) wgmma_st_n192_t0(acc, dw0 + ks * 128, do0 + ks * 16, (hh > 0 || ks > 0) ? 1 : 0);
      wg_commit();
      if (hh > 0) { wg_wait<1>(); release(pw1); release(po2); }
      const uint64_t do1 = desc_kmajor_nosw(next(so1));
      const uint64_t dw1 = desc_mnmajor_sw128<1024>(next(sw1) + wg * 12288);
      wg_fence();
      wgmma_st_n192_t0(acc, dw0 + 4 * 128, do1, 1);
      wgmma_st_n192_t0(acc, dw0 + 5 * 128, do1 + 16, 1);
      wgmma_st_n192_t0(acc, dw1, do1 + 32, 1);
      wgmma_st_n192_t0(acc, dw1 + 128, do1 + 48, 1);
      wg_commit();
      wg_wait<1>(); release(so0);
      const uint64_t do2 = desc_kmajor_nosw(next(so2));
      wg_fence();
#pragma unroll
      for (int ks = 0; ks < 4; ks++) wgmma_st_n192_t0(acc, dw1 + (2 + ks) * 128, do2 + ks * 16, 1);
      wg_commit();
      wg_wait<1>(); release(sw0); release(so1);
      pw1 = sw1; po2 = so2;
    }
    wg_wait<0>();
    touch(acc);
    float4* part = g_part[par] + (size_t)(tile * 2 + wg) * 24 * 128 + tid;
    if (!fin) {
#pragma unroll
      for (int j = 0; j < 24; j++)
        asm volatile("red.global.add.v4.f32 [%0], {%1, %2, %3, %4};" :: "l"(part + j * 128), "f"(acc[4 * j]), "f"(acc[4 * j + 1]), "f"(acc[4 * j + 2]), "f"(acc[4 * j + 3]) : "memory");
      __threadfence();
      __syncwarp();
      if (lane == 0) atomicAdd(&g_tile_cnt[tile], 1u);
      for (int i = (int)(ent >> 23) * 256 + (int)threadIdx.x - 128; i < 40 * 2 * 24 * 128; i += (N_CTA2 - 40) * 256)
        __stcg(g_part[par ^ 1] + i, make_float4(0.f, 0.f, 0.f, 0.f));
    } else {
      release(pw1); release(po2);
      asm volatile("bar.sync 3, 256;" ::: "memory");
      uint32_t sl, pa[4];
#pragma unroll
      for (int q = 0; q < 4; q++) {
        pa[q] = sbase + s * SLOT;
        if ((q >> 1) == wg) next(sl); else if (++s == NS2) { s = 0; ph ^= 1; }
      }
      const uint32_t s1 = s + 1 == NS2 ? 0 : s + 1;
      const uint32_t stg = sbase + (wg ? s1 : s) * SLOT;
      const int q = lane & 3;
      const bool odd = (lane >> 2) & 1;
      const int r8 = 2 * q + (odd ? 1 : 0);
      const uint32_t w0a = stg + r8 * 128 + (((2 * w) ^ r8) << 4) + (lane >> 3) * 4, w1a = stg + r8 * 128 + (((2 * w + 1) ^ r8) << 4) + (lane >> 3) * 4;
      const uint32_t p0 = (wg ? pa[2] : pa[0]) + tid * 16, p1 = (wg ? pa[3] : pa[1]) + tid * 16;
#pragma unroll
      for (int j = 0; j < 24; j++) {
        float4 e;
        asm volatile("ld.shared.v4.f32 {%0, %1, %2, %3}, [%4];" : "=f"(e.x), "=f"(e.y), "=f"(e.z), "=f"(e.w) : "r"((j < 12 ? p0 : p1) + (j % 12) * 2048) : "memory");
        const float x = acc[4 * j] + e.x, y = acc[4 * j + 1] + e.y, z = acc[4 * j + 2] + e.z, u = acc[4 * j + 3] + e.w;
        const float rx = __shfl_xor_sync(0xffffffffu, odd ? x : y, 4), rz = __shfl_xor_sync(0xffffffffu, odd ? z : u, 4);
        asm volatile("st.shared.b32 [%0], %1;" :: "r"(w0a + j * 1024), "r"(odd ? pack_bf16(rx, y) : pack_bf16(x, rx)) : "memory");
        asm volatile("st.shared.b32 [%0], %1;" :: "r"(w1a + j * 1024), "r"(odd ? pack_bf16(rz, u) : pack_bf16(z, rz)) : "memory");
      }
      asm volatile("bar.sync %0, 128;" :: "r"(1 + wg) : "memory");
      uint8_t* ob = reinterpret_cast<uint8_t*>(out + (size_t)(pr * 192) * (2 * DM) + blk * DM + nt * 128 + wg * 64);
#pragma unroll
      for (int i = 0; i < 12; i++) {
        const int row = i * 16 + (tid >> 3), ck = tid & 7;
        uint4 v;
        asm volatile("ld.shared.v4.b32 {%0, %1, %2, %3}, [%4];" : "=r"(v.x), "=r"(v.y), "=r"(v.z), "=r"(v.w) : "r"(stg + row * 128 + ((ck ^ (row & 7)) << 4)) : "memory");
        *reinterpret_cast<uint4*>(ob + (size_t)row * (4 * DM) + ck * 16) = v;
      }
    }
  }
}

typedef CUresult (*EncodeFn)(CUtensorMap*, CUtensorMapDataType, cuuint32_t, void*, const cuuint64_t*, const cuuint64_t*, const cuuint32_t*, const cuuint32_t*,
                             CUtensorMapInterleave, CUtensorMapSwizzle, CUtensorMapL2promotion, CUtensorMapFloatOOBfill);

void make_map(EncodeFn fn, CUtensorMap* m, const void* ptr, int rank, const uint64_t* dims, const uint64_t* strides, const uint32_t* box) {
  cuuint32_t es[4] = {1, 1, 1, 1};
  fn(m, CU_TENSOR_MAP_DATA_TYPE_BFLOAT16, rank, const_cast<void*>(ptr), dims, strides, box, es, CU_TENSOR_MAP_INTERLEAVE_NONE,
     CU_TENSOR_MAP_SWIZZLE_128B, CU_TENSOR_MAP_L2_PROMOTION_L2_256B, CU_TENSOR_MAP_FLOAT_OOB_FILL_NONE);
}

}

extern "C" void kernel_launch(void* const* d_in, const int* in_sizes, int n_in, void* d_out, int out_size) {
  static Maps maps;
  static const void* cached[10] = {nullptr};
  static bool init = false;
  static int grid = NCTA;
  bool same = init;
  for (int i = 0; i < 10; i++) same = same && (cached[i] == d_in[i]);
  if (!same) {
    void* fnp = nullptr;
    cudaDriverEntryPointQueryResult qr;
    cudaGetDriverEntryPoint("cuTensorMapEncodeTiled", &fnp, cudaEnableDefault, &qr);
    EncodeFn fn = (EncodeFn)fnp;
    for (int b = 0; b < 2; b++) {
      const void* x = d_in[5 * b + 0]; const void* k = d_in[5 * b + 1]; const void* v = d_in[5 * b + 2];
      const void* wq = d_in[5 * b + 3]; const void* wo = d_in[5 * b + 4];
      { uint64_t d[2] = {DM, NB * SQ}; uint64_t s[1] = {DM * 2}; uint32_t bx[2] = {64, 192}; make_map(fn, &maps.x[b], x, 2, d, s, bx);
        uint32_t b1[2] = {64, 96}; make_map(fn, &maps.x1[b], x, 2, d, s, b1); }
      { uint64_t d[4] = {64, 8, NH * DH / 64, DM / 8}; uint64_t s[3] = {NH * DH * 2, 128, 8 * NH * DH * 2}; uint32_t bx[4] = {64, 8, 3, 8}; make_map(fn, &maps.wq[b], wq, 4, d, s, bx); }
      { uint64_t d[4] = {64, 8, 3, (uint64_t)NB * NH * SK / 8}; uint64_t s[3] = {DH * 2, 128, 8 * DH * 2}; uint32_t bx[4] = {64, 8, 3, 8};
        make_map(fn, &maps.k[b], k, 4, d, s, bx); make_map(fn, &maps.v[b], v, 4, d, s, bx); }
      { uint64_t d[3] = {64, NH * DH, DM / 64}; uint64_t s[2] = {DM * 2, 128}; uint32_t bx[3] = {64, 96, 2}; make_map(fn, &maps.wo[b], wo, 3, d, s, bx); }
    }
    {
      const int b4[5] = {CHB4}, b5[6] = {CHB5};
      int n = 0, nz = 0;
      auto add = [&](int blk, int tl, int h0, int h1, int nch) { maps.otab[n++] = blk | (tl << 1) | (h0 << 6) | ((h1 - h0) << 12) | (nch << 18) | ((h1 == NH) << 22) | ((h1 == NH ? 0u : (unsigned)nz++) << 23); };
      for (int tl = 0; tl < 20; tl++) add(0, tl, 0, tl < AX ? 16 : AE, 2);
      for (int tl = 0; tl < 20; tl++) add(0, tl, tl < AX ? 16 : AE, 32, 2);
      for (int c = 0; c < 5; c++)
        for (int tl = 19; tl >= 0; tl--) {
          if (tl < B5) add(1, tl, b5[c], b5[c + 1], 5);
          else if (c < 3) add(1, tl, b4[c], b4[c + 1], 4);
          else if (c == 4) add(1, tl, b4[3], b4[4], 4);
        }
    }
    cudaFuncSetAttribute(attn_kernel, cudaFuncAttributeMaxDynamicSharedMemorySize, SMEM_BYTES);
    cudaFuncSetAttribute(oproj_kernel, cudaFuncAttributeMaxDynamicSharedMemorySize, SMEM2_BYTES);
    int dev = 0, sms = NCTA;
    cudaGetDevice(&dev);
    cudaDeviceGetAttribute(&sms, cudaDevAttrMultiProcessorCount, dev);
    grid = sms < NCTA ? sms : NCTA;
    for (int i = 0; i < 10; i++) cached[i] = d_in[i];
    init = true;
  }
  attn_kernel<<<grid, 384, SMEM_BYTES>>>(maps);
  cudaLaunchConfig_t cfg = {};
  cfg.gridDim = dim3(N_CTA2); cfg.blockDim = dim3(384); cfg.dynamicSmemBytes = SMEM2_BYTES; cfg.stream = cudaStreamPerThread;
  cudaLaunchAttribute at[1];
  at[0].id = cudaLaunchAttributeProgrammaticStreamSerialization; at[0].val.programmaticStreamSerializationAllowed = PDL;
  cfg.attrs = at; cfg.numAttrs = 1;
  cudaLaunchKernelEx(&cfg, oproj_kernel, maps, (__nv_bfloat16*)d_out);
}
```

```cpp
#include <cuda_runtime.h>
#include <cuda_bf16.h>
#include <cuda.h>
#include <stdint.h>

namespace {

constexpr int NB = 8, SQ = 96, DM = 640, NH = 32, SK = 512, DH = 192;
constexpr int SLOT = 24576;
constexpr int NSLOT = 8;
constexpr int SMEM_BYTES = NSLOT * SLOT + SLOT   + 1024   + 256  ;

#define NCTA 132
#define N_ATT 66
#define NPAIR 208
#define FETCH_AHEAD 3
#define KV_INFLIGHT 8
#define WQ_EF 2
#define N_OD 20
#define L2PROMO CU_TENSOR_MAP_L2_PROMOTION_NONE
#define KVPOL 0
#define PDL 1
constexpr int N_TICKETS = NPAIR + 2 * (256 - NPAIR) + (NCTA - N_ATT) / 2;

struct Maps { CUtensorMap x[2], x1[2], wq[2], k[2], v[2], wo[2]; uint32_t otab[140]; };

__device__ uint4 g_stash[2 * NH * NB * 2304];
__device__ float4 g_part[2][40 * 2 * 24 * 128];
__device__ unsigned int g_epoch;
__device__ unsigned int g_tile_cnt[40];
__device__ unsigned int g_flag[2 * NB * NH];
__device__ unsigned int g_ticket, g_done, g_done2;

#define STAMP(i, tk)

__device__ __forceinline__ uint32_t smem_u32(const void* p) { return (uint32_t)__cvta_generic_to_shared(p); }
__device__ __forceinline__ void mbar_init(uint32_t bar, int cnt) { asm volatile("mbarrier.init.shared::cta.b64 [%0], %1;" :: "r"(bar), "r"(cnt) : "memory"); }
__device__ __forceinline__ void mbar_expect_tx(uint32_t bar, uint32_t bytes) { asm volatile("mbarrier.arrive.expect_tx.shared::cta.b64 _, [%0], %1;" :: "r"(bar), "r"(bytes) : "memory"); }
__device__ __forceinline__ void mbar_arrive(uint32_t bar) { asm volatile("mbarrier.arrive.shared::cta.b64 _, [%0];" :: "r"(bar) : "memory"); }
__device__ __forceinline__ void mbar_wait(uint32_t bar, uint32_t parity) {
  asm volatile("{\n.reg .pred p;\nWAIT_%=:\nmbarrier.try_wait.parity.shared::cta.b64 p, [%0], %1;\n@p bra DONE_%=;\nbra WAIT_%=;\nDONE_%=:\n}" :: "r"(bar), "r"(parity) : "memory");
}
__device__ __forceinline__ void tma_2d(uint32_t dst, const CUtensorMap* m, int c0, int c1, uint32_t bar) {
  asm volatile("cp.async.bulk.tensor.2d.shared::cluster.global.mbarrier::complete_tx::bytes [%0], [%1, {%3, %4}], [%2];"
               :: "r"(dst), "l"(m), "r"(bar), "r"(c0), "r"(c1) : "memory");
}
__device__ __forceinline__ void tma_3d(uint32_t dst, const CUtensorMap* m, int c0, int c1, int c2, uint32_t bar) {
  asm volatile("cp.async.bulk.tensor.3d.shared::cluster.global.mbarrier::complete_tx::bytes [%0], [%1, {%3, %4, %5}], [%2];"
               :: "r"(dst), "l"(m), "r"(bar), "r"(c0), "r"(c1), "r"(c2) : "memory");
}
__device__ __forceinline__ void tma_4d(uint32_t dst, const CUtensorMap* m, int c2, int c3, uint32_t bar) {
  asm volatile("cp.async.bulk.tensor.4d.shared::cluster.global.mbarrier::complete_tx::bytes [%0], [%1, {%3, %3, %4, %5}], [%2];"
               :: "r"(dst), "l"(m), "r"(bar), "r"(0), "r"(c2), "r"(c3) : "memory");
}
__device__ __forceinline__ void tma_4d_hint(uint32_t dst, const CUtensorMap* m, int c2, int c3, uint32_t bar, uint64_t pol) {
  asm volatile("cp.async.bulk.tensor.4d.shared::cluster.global.mbarrier::complete_tx::bytes.L2::cache_hint [%0], [%1, {%3, %3, %4, %5}], [%2], %6;"
               :: "r"(dst), "l"(m), "r"(bar), "r"(0), "r"(c2), "r"(c3), "l"(pol) : "memory");
}
__device__ __forceinline__ void bulk_load(uint32_t dst, const void* src, uint32_t bytes, uint32_t bar) {
  asm volatile("cp.async.bulk.shared::cluster.global.mbarrier::complete_tx::bytes [%0], [%1], %2, [%3];" :: "r"(dst), "l"(src), "r"(bytes), "r"(bar) : "memory");
}
__device__ __forceinline__ void wg_fence() { asm volatile("wgmma.fence.sync.aligned;" ::: "memory"); }
__device__ __forceinline__ void wg_commit() { asm volatile("wgmma.commit_group.sync.aligned;" ::: "memory"); }
template <int N> __device__ __forceinline__ void wg_wait() { asm volatile("wgmma.wait_group.sync.aligned %0;" :: "n"(N) : "memory"); }
template <int N> __device__ __forceinline__ void touch(float (&d)[N]) {
#pragma unroll
  for (int i = 0; i < N; i++) asm volatile("" : "+f"(d[i]) :: "memory");
}
template <int N> __device__ __forceinline__ void touch_u(uint32_t (&d)[N]) {
#pragma unroll
  for (int i = 0; i < N; i++) asm volatile("" : "+r"(d[i]) :: "memory");
}
__device__ __forceinline__ float ex2(float x) { float y; asm("ex2.approx.ftz.f32 %0, %1;" : "=f"(y) : "f"(x)); return y; }
__device__ __forceinline__ uint32_t pack_bf16(float lo, float hi) { uint32_t r; asm("cvt.rn.bf16x2.f32 %0, %1, %2;" : "=r"(r) : "f"(hi), "f"(lo)); return r; }

constexpr uint64_t DESC_SW128 = (uint64_t)1 << 62;
__device__ __forceinline__ uint64_t desc_kmajor_sw128(uint32_t addr) {
  return DESC_SW128 | ((uint64_t)(1024 >> 4) << 32) | ((uint64_t)1 << 16) | (uint64_t)((addr & 0x3FFFF) >> 4);
}
__device__ __forceinline__ uint64_t desc_k_il(uint32_t addr) {
  return DESC_SW128 | ((uint64_t)(3072 >> 4) << 32) | ((uint64_t)1 << 16) | (uint64_t)((addr & 0x3FFFF) >> 4);
}
__device__ __forceinline__ uint64_t desc_mn_il(uint32_t addr) {
  return DESC_SW128 | ((uint64_t)(3072 >> 4) << 32) | ((uint64_t)(1024 >> 4) << 16) | (uint64_t)((addr & 0x3FFFF) >> 4);
}
template <int LBO> __device__ __forceinline__ uint64_t desc_mnmajor_sw128(uint32_t addr) {
  return DESC_SW128 | ((uint64_t)(1024 >> 4) << 32) | ((uint64_t)(LBO >> 4) << 16) | (uint64_t)((addr & 0x3FFFF) >> 4);
}
__device__ __forceinline__ uint64_t desc_kmajor_nosw(uint32_t addr) {
  return ((uint64_t)(1024 >> 4) << 32) | ((uint64_t)(128 >> 4) << 16) | (uint64_t)((addr & 0x3FFFF) >> 4);
}

__device__ __forceinline__ void wgmma_rs_n64_t0(float (&d)[32], uint32_t a0, uint32_t a1, uint32_t a2, uint32_t a3, uint64_t descB, int scaleD) {
  asm volatile("{\n.reg .pred p;\nsetp.ne.b32 p, %37, 0;\n"
    "wgmma.mma_async.sync.aligned.m64n64k16.f32.bf16.bf16 "
    "{%0, %1, %2, %3, %4, %5, %6, %7, %8, %9, %10, %11, %12, %13, %14, %15, %16, %17, %18, %19, %20, %21, %22, %23, %24, %25, %26, %27, %28, %29, %30, %31}, "
    "{%32, %33, %34, %35}, %36, p, 1, 1, 0;\n}\n"
    : "+f"(d[0]), "+f"(d[1]), "+f"(d[2]), "+f"(d[3]), "+f"(d[4]), "+f"(d[5]), "+f"(d[6]), "+f"(d[7]), "+f"(d[8]), "+f"(d[9]), "+f"(d[10]), "+f"(d[11]), "+f"(d[12]), "+f"(d[13]), "+f"(d[14]), "+f"(d[15]), "+f"(d[16]), "+f"(d[17]), "+f"(d[18]), "+f"(d[19]), "+f"(d[20]), "+f"(d[21]), "+f"(d[22]), "+f"(d[23]), "+f"(d[24]), "+f"(d[25]), "+f"(d[26]), "+f"(d[27]), "+f"(d[28]), "+f"(d[29]), "+f"(d[30]), "+f"(d[31])
    : "r"(a0), "r"(a1), "r"(a2), "r"(a3), "l"(descB), "r"(scaleD));
}
__device__ __forceinline__ void wgmma_rs_n192_t1(float (&d)[96], uint32_t a0, uint32_t a1, uint32_t a2, uint32_t a3, uint64_t descB, int scaleD) {
  asm volatile("{\n.reg .pred p;\nsetp.ne.b32 p, %101, 0;\n"
    "wgmma.mma_async.sync.aligned.m64n192k16.f32.bf16.bf16 "
    "{%0, %1, %2, %3, %4, %5, %6, %7, %8, %9, %10, %11, %12, %13, %14, %15, %16, %17, %18, %19, %20, %21, %22, %23, %24, %25, %26, %27, %28, %29, %30, %31, %32, %33, %34, %35, %36, %37, %38, %39, %40, %41, %42, %43, %44, %45, %46, %47, %48, %49, %50, %51, %52, %53, %54, %55, %56, %57, %58, %59, %60, %61, %62, %63, %64, %65, %66, %67, %68, %69, %70, %71, %72, %73, %74, %75, %76, %77, %78, %79, %80, %81, %82, %83, %84, %85, %86, %87, %88, %89, %90, %91, %92, %93, %94, %95}, "
    "{%96, %97, %98, %99}, %100, p, 1, 1, 1;\n}\n"
    : "+f"(d[0]), "+f"(d[1]), "+f"(d[2]), "+f"(d[3]), "+f"(d[4]), "+f"(d[5]), "+f"(d[6]), "+f"(d[7]), "+f"(d[8]), "+f"(d[9]), "+f"(d[10]), "+f"(d[11]), "+f"(d[12]), "+f"(d[13]), "+f"(d[14]), "+f"(d[15]), "+f"(d[16]), "+f"(d[17]), "+f"(d[18]), "+f"(d[19]), "+f"(d[20]), "+f"(d[21]), "+f"(d[22]), "+f"(d[23]), "+f"(d[24]), "+f"(d[25]), "+f"(d[26]), "+f"(d[27]), "+f"(d[28]), "+f"(d[29]), "+f"(d[30]), "+f"(d[31]), "+f"(d[32]), "+f"(d[33]), "+f"(d[34]), "+f"(d[35]), "+f"(d[36]), "+f"(d[37]), "+f"(d[38]), "+f"(d[39]), "+f"(d[40]), "+f"(d[41]), "+f"(d[42]), "+f"(d[43]), "+f"(d[44]), "+f"(d[45]), "+f"(d[46]), "+f"(d[47]), "+f"(d[48]), "+f"(d[49]), "+f"(d[50]), "+f"(d[51]), "+f"(d[52]), "+f"(d[53]), "+f"(d[54]), "+f"(d[55]), "+f"(d[56]), "+f"(d[57]), "+f"(d[58]), "+f"(d[59]), "+f"(d[60]), "+f"(d[61]), "+f"(d[62]), "+f"(d[63]), "+f"(d[64]), "+f"(d[65]), "+f"(d[66]), "+f"(d[67]), "+f"(d[68]), "+f"(d[69]), "+f"(d[70]), "+f"(d[71]), "+f"(d[72]), "+f"(d[73]), "+f"(d[74]), "+f"(d[75]), "+f"(d[76]), "+f"(d[77]), "+f"(d[78]), "+f"(d[79]), "+f"(d[80]), "+f"(d[81]), "+f"(d[82]), "+f"(d[83]), "+f"(d[84]), "+f"(d[85]), "+f"(d[86]), "+f"(d[87]), "+f"(d[88]), "+f"(d[89]), "+f"(d[90]), "+f"(d[91]), "+f"(d[92]), "+f"(d[93]), "+f"(d[94]), "+f"(d[95])
    : "r"(a0), "r"(a1), "r"(a2), "r"(a3), "l"(descB), "r"(scaleD));
}
__device__ __forceinline__ void wgmma_ss_n192_t1(float (&d)[96], uint64_t descA, uint64_t descB, int scaleD) {
  asm volatile("{\n.reg .pred p;\nsetp.ne.b32 p, %98, 0;\n"
    "wgmma.mma_async.sync.aligned.m64n192k16.f32.bf16.bf16 "
    "{%0, %1, %2, %3, %4, %5, %6, %7, %8, %9, %10, %11, %12, %13, %14, %15, %16, %17, %18, %19, %20, %21, %22, %23, %24, %25, %26, %27, %28, %29, %30, %31, %32, %33, %34, %35, %36, %37, %38, %39, %40, %41, %42, %43, %44, %45, %46, %47, %48, %49, %50, %51, %52, %53, %54, %55, %56, %57, %58, %59, %60, %61, %62, %63, %64, %65, %66, %67, %68, %69, %70, %71, %72, %73, %74, %75, %76, %77, %78, %79, %80, %81, %82, %83, %84, %85, %86, %87, %88, %89, %90, %91, %92, %93, %94, %95}, "
    "%96, %97, p, 1, 1, 0, 1;\n}\n"
    : "+f"(d[0]), "+f"(d[1]), "+f"(d[2]), "+f"(d[3]), "+f"(d[4]), "+f"(d[5]), "+f"(d[6]), "+f"(d[7]), "+f"(d[8]), "+f"(d[9]), "+f"(d[10]), "+f"(d[11]), "+f"(d[12]), "+f"(d[13]), "+f"(d[14]), "+f"(d[15]), "+f"(d[16]), "+f"(d[17]), "+f"(d[18]), "+f"(d[19]), "+f"(d[20]), "+f"(d[21]), "+f"(d[22]), "+f"(d[23]), "+f"(d[24]), "+f"(d[25]), "+f"(d[26]), "+f"(d[27]), "+f"(d[28]), "+f"(d[29]), "+f"(d[30]), "+f"(d[31]), "+f"(d[32]), "+f"(d[33]), "+f"(d[34]), "+f"(d[35]), "+f"(d[36]), "+f"(d[37]), "+f"(d[38]), "+f"(d[39]), "+f"(d[40]), "+f"(d[41]), "+f"(d[42]), "+f"(d[43]), "+f"(d[44]), "+f"(d[45]), "+f"(d[46]), "+f"(d[47]), "+f"(d[48]), "+f"(d[49]), "+f"(d[50]), "+f"(d[51]), "+f"(d[52]), "+f"(d[53]), "+f"(d[54]), "+f"(d[55]), "+f"(d[56]), "+f"(d[57]), "+f"(d[58]), "+f"(d[59]), "+f"(d[60]), "+f"(d[61]), "+f"(d[62]), "+f"(d[63]), "+f"(d[64]), "+f"(d[65]), "+f"(d[66]), "+f"(d[67]), "+f"(d[68]), "+f"(d[69]), "+f"(d[70]), "+f"(d[71]), "+f"(d[72]), "+f"(d[73]), "+f"(d[74]), "+f"(d[75]), "+f"(d[76]), "+f"(d[77]), "+f"(d[78]), "+f"(d[79]), "+f"(d[80]), "+f"(d[81]), "+f"(d[82]), "+f"(d[83]), "+f"(d[84]), "+f"(d[85]), "+f"(d[86]), "+f"(d[87]), "+f"(d[88]), "+f"(d[89]), "+f"(d[90]), "+f"(d[91]), "+f"(d[92]), "+f"(d[93]), "+f"(d[94]), "+f"(d[95])
    : "l"(descA), "l"(descB), "r"(scaleD));
}
__device__ __forceinline__ void wgmma_ss_n64_t1(float (&d)[32], uint64_t descA, uint64_t descB, int scaleD) {
  asm volatile("{\n.reg .pred p;\nsetp.ne.b32 p, %34, 0;\n"
    "wgmma.mma_async.sync.aligned.m64n64k16.f32.bf16.bf16 "
    "{%0, %1, %2, %3, %4, %5, %6, %7, %8, %9, %10, %11, %12, %13, %14, %15, %16, %17, %18, %19, %20, %21, %22, %23, %24, %25, %26, %27, %28, %29, %30, %31}, "
    "%32, %33, p, 1, 1, 0, 1;\n}\n"
    : "+f"(d[0]), "+f"(d[1]), "+f"(d[2]), "+f"(d[3]), "+f"(d[4]), "+f"(d[5]), "+f"(d[6]), "+f"(d[7]), "+f"(d[8]), "+f"(d[9]), "+f"(d[10]), "+f"(d[11]), "+f"(d[12]), "+f"(d[13]), "+f"(d[14]), "+f"(d[15]), "+f"(d[16]), "+f"(d[17]), "+f"(d[18]), "+f"(d[19]), "+f"(d[20]), "+f"(d[21]), "+f"(d[22]), "+f"(d[23]), "+f"(d[24]), "+f"(d[25]), "+f"(d[26]), "+f"(d[27]), "+f"(d[28]), "+f"(d[29]), "+f"(d[30]), "+f"(d[31])
    : "l"(descA), "l"(descB), "r"(scaleD));
}
__device__ __forceinline__ void wgmma_ss_n32_t1(float (&d)[16], uint64_t descA, uint64_t descB, int scaleD) {
  asm volatile("{\n.reg .pred p;\nsetp.ne.b32 p, %18, 0;\n"
    "wgmma.mma_async.sync.aligned.m64n32k16.f32.bf16.bf16 "
    "{%0, %1, %2, %3, %4, %5, %6, %7, %8, %9, %10, %11, %12, %13, %14, %15}, "
    "%16, %17, p, 1, 1, 0, 1;\n}\n"
    : "+f"(d[0]), "+f"(d[1]), "+f"(d[2]), "+f"(d[3]), "+f"(d[4]), "+f"(d[5]), "+f"(d[6]), "+f"(d[7]), "+f"(d[8]), "+f"(d[9]), "+f"(d[10]), "+f"(d[11]), "+f"(d[12]), "+f"(d[13]), "+f"(d[14]), "+f"(d[15])
    : "l"(descA), "l"(descB), "r"(scaleD));
}
__device__ __forceinline__ void wgmma_st_n192_t0(float (&d)[96], uint64_t descA, uint64_t descB, int scaleD) {
  asm volatile("{\n.reg .pred p;\nsetp.ne.b32 p, %98, 0;\n"
    "wgmma.mma_async.sync.aligned.m64n192k16.f32.bf16.bf16 "
    "{%0, %1, %2, %3, %4, %5, %6, %7, %8, %9, %10, %11, %12, %13, %14, %15, %16, %17, %18, %19, %20, %21, %22, %23, %24, %25, %26, %27, %28, %29, %30, %31, %32, %33, %34, %35, %36, %37, %38, %39, %40, %41, %42, %43, %44, %45, %46, %47, %48, %49, %50, %51, %52, %53, %54, %55, %56, %57, %58, %59, %60, %61, %62, %63, %64, %65, %66, %67, %68, %69, %70, %71, %72, %73, %74, %75, %76, %77, %78, %79, %80, %81, %82, %83, %84, %85, %86, %87, %88, %89, %90, %91, %92, %93, %94, %95}, "
    "%96, %97, p, 1, 1, 1, 0;\n}\n"
    : "+f"(d[0]), "+f"(d[1]), "+f"(d[2]), "+f"(d[3]), "+f"(d[4]), "+f"(d[5]), "+f"(d[6]), "+f"(d[7]), "+f"(d[8]), "+f"(d[9]), "+f"(d[10]), "+f"(d[11]), "+f"(d[12]), "+f"(d[13]), "+f"(d[14]), "+f"(d[15]), "+f"(d[16]), "+f"(d[17]), "+f"(d[18]), "+f"(d[19]), "+f"(d[20]), "+f"(d[21]), "+f"(d[22]), "+f"(d[23]), "+f"(d[24]), "+f"(d[25]), "+f"(d[26]), "+f"(d[27]), "+f"(d[28]), "+f"(d[29]), "+f"(d[30]), "+f"(d[31]), "+f"(d[32]), "+f"(d[33]), "+f"(d[34]), "+f"(d[35]), "+f"(d[36]), "+f"(d[37]), "+f"(d[38]), "+f"(d[39]), "+f"(d[40]), "+f"(d[41]), "+f"(d[42]), "+f"(d[43]), "+f"(d[44]), "+f"(d[45]), "+f"(d[46]), "+f"(d[47]), "+f"(d[48]), "+f"(d[49]), "+f"(d[50]), "+f"(d[51]), "+f"(d[52]), "+f"(d[53]), "+f"(d[54]), "+f"(d[55]), "+f"(d[56]), "+f"(d[57]), "+f"(d[58]), "+f"(d[59]), "+f"(d[60]), "+f"(d[61]), "+f"(d[62]), "+f"(d[63]), "+f"(d[64]), "+f"(d[65]), "+f"(d[66]), "+f"(d[67]), "+f"(d[68]), "+f"(d[69]), "+f"(d[70]), "+f"(d[71]), "+f"(d[72]), "+f"(d[73]), "+f"(d[74]), "+f"(d[75]), "+f"(d[76]), "+f"(d[77]), "+f"(d[78]), "+f"(d[79]), "+f"(d[80]), "+f"(d[81]), "+f"(d[82]), "+f"(d[83]), "+f"(d[84]), "+f"(d[85]), "+f"(d[86]), "+f"(d[87]), "+f"(d[88]), "+f"(d[89]), "+f"(d[90]), "+f"(d[91]), "+f"(d[92]), "+f"(d[93]), "+f"(d[94]), "+f"(d[95])
    : "l"(descA), "l"(descB), "r"(scaleD));
}

__device__ __forceinline__ unsigned int ld_acquire(const unsigned int* p) { unsigned int v; asm volatile("ld.acquire.gpu.global.u32 %0, [%1];" : "=r"(v) : "l"(p) : "memory"); return v; }

struct Cons {
  uint32_t base, full0;
  uint32_t it;
  int lane;
  __device__ __forceinline__ uint32_t wait(uint32_t slot, uint32_t u) const { mbar_wait(full0 + slot * 8, (u >> 3) & 1); return base + slot * SLOT; }
  __device__ __forceinline__ uint32_t wait(uint32_t u) const { return wait(u & 7, u); }
  __device__ __forceinline__ void release(uint32_t slot) const { if (lane == 0) mbar_arrive(full0 + 64 + (slot & 7) * 8); }
};

__device__ __forceinline__ int ticket_task(int ticket) {
  int u = ticket, f = 0;
  if (ticket >= N_ATT) {
    if (ticket < NCTA) { const int s = ticket - N_ATT; u = N_ATT + (s >> 1); f = 1 | ((s & 1) << 2); }
    else {
      u = ticket - (NCTA - N_ATT) / 2;
      if (u >= NPAIR) { const int s = u - NPAIR; u = NPAIR + (s >> 1); f = 1 | ((s & 1) << 2); }
    }
  }
  const int hh = u & 7, pr = (u >> 3) & 3, g = (u >> 5) & 3, blk = u >> 7;
  return f | (pr << 3) | ((g * 8 + hh) << 5) | (blk << 10);
}

__device__ __forceinline__ void qproj(Cons& r, uint32_t (&qf)[48], uint32_t park, bool pair, int wg, int tid) {
  float acc[96];
  float acx[32];
  float acy[16];
  for (int c = 0; c < 10; c++) {
    const uint32_t sx = r.it;
    const uint32_t xa = r.wait(sx), wa = r.wait(sx + 1);
    const uint64_t da = desc_kmajor_sw128(xa + wg * 8192), d2 = desc_kmajor_sw128(xa + 2 * 8192);
    const uint64_t db = desc_mn_il(wa), dbx = desc_mn_il(wa + wg * 1024), dby = desc_mn_il(wa + 2048 + wg * 64);
    if (pair) {
      wg_fence();
#pragma unroll
      for (int ks = 0; ks < 4; ks++) {
        const int sc = (c > 0 || ks > 0) ? 1 : 0;
        wgmma_ss_n192_t1(acc, da + ks * 2, db + ks * 384, sc);
        wgmma_ss_n64_t1(acx, d2 + ks * 2, dbx + ks * 384, sc);
        wgmma_ss_n32_t1(acy, d2 + ks * 2, dby + ks * 384, sc);
      }
      wg_commit();
    } else {
      wg_fence();
#pragma unroll
      for (int ks = 0; ks < 4; ks++)
        wgmma_ss_n192_t1(acc, da + ks * 2, db + ks * 384, (c > 0 || ks > 0) ? 1 : 0);
      wg_commit();
    }
    if (c > 0) { wg_wait<1>(); r.release((sx + 6) & 7); r.release((sx + 7) & 7); }
    r.it += 2;
  }
  wg_wait<0>();
  touch(acc); touch(acx); touch(acy);
  r.release((r.it + 6) & 7); r.release((r.it + 7) & 7);
  if (pair) {
#pragma unroll
    for (int ks = 0; ks < 4; ks++) {
      uint32_t a0 = pack_bf16(acx[8 * ks + 0], acx[8 * ks + 1]), a1 = pack_bf16(acx[8 * ks + 2], acx[8 * ks + 3]);
      uint32_t a2 = pack_bf16(acx[8 * ks + 4], acx[8 * ks + 5]), a3 = pack_bf16(acx[8 * ks + 6], acx[8 * ks + 7]);
      asm volatile("st.shared.v4.b32 [%0], {%1, %2, %3, %4};" :: "r"(park + ((wg * 4 + ks) * 128 + tid) * 16), "r"(a0), "r"(a1), "r"(a2), "r"(a3) : "memory");
    }
#pragma unroll
    for (int ks = 0; ks < 2; ks++) {
      uint32_t a0 = pack_bf16(acy[8 * ks + 0], acy[8 * ks + 1]), a1 = pack_bf16(acy[8 * ks + 2], acy[8 * ks + 3]);
      uint32_t a2 = pack_bf16(acy[8 * ks + 4], acy[8 * ks + 5]), a3 = pack_bf16(acy[8 * ks + 6], acy[8 * ks + 7]);
      asm volatile("st.shared.v4.b32 [%0], {%1, %2, %3, %4};" :: "r"(park + ((8 + wg * 2 + ks) * 128 + tid) * 16), "r"(a0), "r"(a1), "r"(a2), "r"(a3) : "memory");
    }
  }
#pragma unroll
  for (int i = 0; i < 48; i++) qf[i] = pack_bf16(acc[2 * i], acc[2 * i + 1]);
}

__device__ __forceinline__ void sched_sync(int wg) { asm volatile("bar.sync %0, 256;" :: "r"(2 + wg) : "memory"); }
__device__ __forceinline__ void sched_arrive(int wg) { asm volatile("bar.arrive %0, 256;" :: "r"(3 - wg) : "memory"); }

__device__ __forceinline__ void issue_qk(float (&s)[32], const uint32_t (&qf)[48], uint64_t dk) {
#pragma unroll
  for (int ks = 0; ks < 12; ks++)
    wgmma_rs_n64_t0(s, qf[4 * ks], qf[4 * ks + 1], qf[4 * ks + 2], qf[4 * ks + 3], dk + ((ks >> 2) * 64 + (ks & 3) * 2), ks > 0);
  wg_commit();
}
__device__ __forceinline__ void attention(Cons& r, const uint32_t (&qf)[48], bool valid, uint32_t* dst, uint32_t sig, int wg) {
  constexpr float CS = 0.07216878364870322f * 1.4426950408889634f;
  const int lane = r.lane;
  float o[96];
  float s[32];
  uint32_t pa[8], pb[8];
  float m0 = -INFINITY, m1 = -INFINITY, l0 = 0.f, l1 = 0.f, al0 = 1.f, al1 = 1.f;
  bool resc = false;
#pragma unroll
  for (int i = 0; i < 8; i++) { pa[i] = 0; pb[i] = 0; }

  auto row_max = [&]() {
    float x0 = fmaxf(s[0], s[1]), x1 = fmaxf(s[2], s[3]), y0 = fmaxf(s[4], s[5]), y1 = fmaxf(s[6], s[7]);
#pragma unroll
    for (int i = 2; i < 8; i += 2) {
      x0 = fmaxf(x0, fmaxf(s[4 * i], s[4 * i + 1])); x1 = fmaxf(x1, fmaxf(s[4 * i + 2], s[4 * i + 3]));
      y0 = fmaxf(y0, fmaxf(s[4 * i + 4], s[4 * i + 5])); y1 = fmaxf(y1, fmaxf(s[4 * i + 6], s[4 * i + 7]));
    }
    x0 = fmaxf(x0, y0); x1 = fmaxf(x1, y1);
    x0 = fmaxf(x0, __shfl_xor_sync(0xffffffffu, x0, 1)); x1 = fmaxf(x1, __shfl_xor_sync(0xffffffffu, x1, 1));
    x0 = fmaxf(x0, __shfl_xor_sync(0xffffffffu, x0, 2)); x1 = fmaxf(x1, __shfl_xor_sync(0xffffffffu, x1, 2));
    resc = __any_sync(0xffffffffu, (x0 - m0) * CS > 8.0f || (x1 - m1) * CS > 8.0f);
    if (resc) {
      const float n0 = fmaxf(m0, x0), n1 = fmaxf(m1, x1);
      al0 = ex2((m0 - n0) * CS); al1 = ex2((m1 - n1) * CS);
      m0 = n0; m1 = n1;
      l0 *= al0; l1 *= al1;
    }
  };
  auto exps = [&](uint32_t (&p)[8], int h) {
    const float c0 = m0 * CS, c1 = m1 * CS;
    float t0 = 0.f, t1 = 0.f;
#pragma unroll
    for (int i = 0; i < 4; i++) {
      const int k = 16 * h + 4 * i;
      const float e0 = ex2(fmaf(s[k], CS, -c0)), e1 = ex2(fmaf(s[k + 1], CS, -c0));
      const float e2 = ex2(fmaf(s[k + 2], CS, -c1)), e3 = ex2(fmaf(s[k + 3], CS, -c1));
      t0 += e0 + e1; t1 += e2 + e3;
      p[2 * i] = pack_bf16(e0, e1); p[2 * i + 1] = pack_bf16(e2, e3);
    }
    l0 += t0; l1 += t1;
  };
  auto pv_a = [&](uint64_t dv, int first) {
    wgmma_rs_n192_t1(o, pa[0], pa[1], pa[2], pa[3], dv, first ? 0 : 1);
    wgmma_rs_n192_t1(o, pa[4], pa[5], pa[6], pa[7], dv + 384, 1);
    wg_commit();
  };
  auto pv_b = [&](uint64_t dv) {
    wgmma_rs_n192_t1(o, pb[0], pb[1], pb[2], pb[3], dv + 768, 1);
    wgmma_rs_n192_t1(o, pb[4], pb[5], pb[6], pb[7], dv + 1152, 1);
    wg_commit();
  };

  if (wg == 1) sched_arrive(1);
  {
    const uint32_t sk = r.it & 7;
    const uint64_t dk = desc_k_il(r.wait(sk, r.it));
    sched_sync(wg);
    wg_fence();
    issue_qk(s, qf, dk);
    sched_arrive(wg);
    wg_wait<0>();
    touch(s);
    r.release(sk);
    if (valid) { row_max(); exps(pa, 0); exps(pb, 1); }
  }
  for (int j = 0; j < 7; j++) {
    const uint32_t u = r.it;
    const uint32_t sv = (u + 1) & 7, sk = (u + 2) & 7;
    const uint64_t dk = desc_k_il(r.wait(sk, u + 2));
    const uint64_t dv = desc_mn_il(r.wait(sv, u + 1));
    sched_sync(wg);
    wg_fence();
    issue_qk(s, qf, dk);
    pv_a(dv, j == 0);
    pv_b(dv);
    sched_arrive(wg);
    wg_wait<2>();
    touch(s);
    r.release(sk);
    if (valid) row_max();
    wg_wait<1>();
    touch_u(pa);
    if (valid) exps(pa, 0);
    touch_u(pa);
    wg_wait<0>();
    touch(o); touch_u(pb);
    r.release(sv);
    if (valid) exps(pb, 1);
    if (resc) {
#pragma unroll
      for (int i = 0; i < 24; i++) { o[4 * i] *= al0; o[4 * i + 1] *= al0; o[4 * i + 2] *= al1; o[4 * i + 3] *= al1; }
    }
    touch_u(pb);
    r.it += 2;
  }
  {
    const uint32_t sv = (r.it + 1) & 7;
    const uint64_t dv = desc_mn_il(r.wait(sv, r.it + 1));
    sched_sync(wg);
    wg_fence();
    pv_a(dv, 0);
    pv_b(dv);
    if (wg == 0) sched_arrive(0);
    wg_wait<0>();
    touch(o); touch_u(pa); touch_u(pb);
    r.release(sv);
    r.it += 2;
  }
  if (valid) {
    l0 += __shfl_xor_sync(0xffffffffu, l0, 1); l1 += __shfl_xor_sync(0xffffffffu, l1, 1);
    l0 += __shfl_xor_sync(0xffffffffu, l0, 2); l1 += __shfl_xor_sync(0xffffffffu, l1, 2);
    const float i0 = 1.0f / l0, i1 = 1.0f / l1;
#pragma unroll
    for (int kc = 0; kc < 24; kc++) {
      dst[(kc >> 3) * 3072 + (kc & 7) * 32 + lane] = pack_bf16(o[4 * kc] * i0, o[4 * kc + 1] * i0);
      dst[(kc >> 3) * 3072 + 256 + (kc & 7) * 32 + lane] = pack_bf16(o[4 * kc + 2] * i1, o[4 * kc + 3] * i1);
    }
    __syncwarp();
    if (lane == 0) mbar_arrive(sig);
  }
}

__global__ void __launch_bounds__(384, 1) attn_kernel(const __grid_constant__ Maps maps) {
  extern __shared__ uint8_t smem_raw[];
  const uint32_t sbase = (smem_u32(smem_raw) + 1023u) & ~1023u;
  const uint32_t park = sbase + NSLOT * SLOT;
  const uint32_t bars = park + SLOT;
  const uint32_t full0 = bars, empty0 = bars + 64;
  const uint32_t tfull0 = bars + 128, tempty0 = bars + 160, sig0 = bars + 192, tbox = bars + 224, sreq = bars + 240;
  const int warp = __shfl_sync(0xffffffffu, threadIdx.x >> 5, 0), lane = threadIdx.x & 31;
  if (threadIdx.x == 0) {
    for (int i = 0; i < NSLOT; i++) { mbar_init(full0 + 8 * i, 1); mbar_init(empty0 + 8 * i, 8); }
    for (int i = 0; i < 4; i++) { mbar_init(tfull0 + 8 * i, 1); mbar_init(tempty0 + 8 * i, 10); mbar_init(sig0 + 8 * i, 6); }
    mbar_init(sreq, 1);
    asm volatile("fence.mbarrier_init.release.cluster;" ::: "memory");
  }
  __syncthreads();
  asm volatile("griddepcontrol.launch_dependents;");

  if (warp < 4) {
    asm volatile("setmaxnreg.dec.sync.aligned.u32 24;");
    if (warp == 0 && lane == 0) {
      uint64_t pol;
      asm volatile("createpolicy.fractional.L2::evict_first.b64 %0, 1.0;" : "=l"(pol));
      uint32_t u = 0;
      auto acquire = [&](uint32_t bytes) -> uint32_t {
        const uint32_t s = u & 7;
        mbar_wait(empty0 + 8 * s, ((u >> 3) & 1) ^ 1);
        mbar_expect_tx(full0 + 8 * s, bytes);
        u++;
        return s;
      };
      for (uint32_t n = 0;; n++) {
        int task;
        mbar_wait(tfull0 + 8 * (n & 3), (n >> 2) & 1);
        asm volatile("ld.shared.b32 %0, [%1];" : "=r"(task) : "r"(tbox + 4 * (n & 3)) : "memory");
        mbar_arrive(tempty0 + 8 * (n & 3));
        if (task < 0) break;
        const int type = task & 3, bsel = (task >> 2) & 1, pr = (task >> 3) & 3, h = (task >> 5) & 31, blk = (task >> 10) & 1;
        if (type != 2) {
          const CUtensorMap* mx = type ? &maps.x1[blk] : &maps.x[blk];
#pragma unroll 1
          for (int c = 0; c < 10; c++) {
            uint32_t s = acquire(type ? SLOT / 2 : SLOT);
            tma_2d(sbase + s * SLOT, mx, c * 64, pr * 192 + bsel * 96, full0 + 8 * s);
            s = acquire(SLOT);
            if (WQ_EF == 1 || (WQ_EF == 2 && pr == 3 && (type == 0 || bsel))) tma_4d_hint(sbase + s * SLOT, &maps.wq[blk], h * 3, c * 8, full0 + 8 * s, pol);
            else tma_4d(sbase + s * SLOT, &maps.wq[blk], h * 3, c * 8, full0 + 8 * s);
          }
        }
        int rg = (((pr * 2 + bsel) * NH + h) * SK) >> 3;
#pragma unroll 1
        for (int j = 0; j < 8; j++) {
          if (j == 8 - FETCH_AHEAD) mbar_arrive(sreq);
          if (KV_INFLIGHT < 8 && u >= KV_INFLIGHT) mbar_wait(full0 + 8 * ((u - KV_INFLIGHT) & 7), ((u - KV_INFLIGHT) >> 3) & 1);
          uint32_t s = acquire(SLOT);
          tma_4d_hint(sbase + s * SLOT, &maps.k[blk], 0, rg, full0 + 8 * s, pol);
          if (KV_INFLIGHT < 8 && u >= KV_INFLIGHT) mbar_wait(full0 + 8 * ((u - KV_INFLIGHT) & 7), ((u - KV_INFLIGHT) >> 3) & 1);
          s = acquire(SLOT);
          tma_4d_hint(sbase + s * SLOT, &maps.v[blk], 0, rg, full0 + 8 * s, pol);
          rg += 8;
        }
      }
    } else if (warp == 1 && lane == 0) {
      int task = ticket_task(blockIdx.x);
      for (uint32_t n = 0;; n++) {
        mbar_wait(tempty0 + 8 * (n & 3), ((n >> 2) & 1) ^ 1);
        asm volatile("st.shared.b32 [%0], %1;" :: "r"(tbox + 4 * (n & 3)), "r"(task) : "memory");
        mbar_arrive(tfull0 + 8 * (n & 3));
        if (task < 0) break;
        if ((task & 3) == 0) {
          task |= 2 | 4;
        } else {
          mbar_wait(sreq, n & 1);
          if ((int)blockIdx.x < N_OD) { task = -1; continue; }
          const unsigned int tk = atomicAdd(&g_ticket, 1u) + gridDim.x;
          task = tk < (unsigned)N_TICKETS ? ticket_task((int)tk) : -1;
          continue;
        }
        mbar_wait(sreq, n & 1);
      }
      __threadfence();
      if (atomicAdd(&g_done, 1u) == gridDim.x - 1) { g_ticket = 0; g_done = 0; }
    } else if (warp == 2 && lane == 0) {
      for (uint32_t n = 0;; n++) {
        int task;
        mbar_wait(tfull0 + 8 * (n & 3), (n >> 2) & 1);
        asm volatile("ld.shared.b32 %0, [%1];" : "=r"(task) : "r"(tbox + 4 * (n & 3)) : "memory");
        if (task < 0) break;
        mbar_wait(sig0 + 8 * (n & 3), (n >> 2) & 1);
        mbar_arrive(tempty0 + 8 * (n & 3));
        __threadfence();
        const int b = ((task >> 3) & 3) * 2 + ((task >> 2) & 1), h = (task >> 5) & 31, blk = (task >> 10) & 1;
        asm volatile("st.release.gpu.global.u32 [%0], %1;" :: "l"(&g_flag[(blk * NB + b) * NH + h]), "r"(6u) : "memory");
      }
    }
  } else {
    asm volatile("setmaxnreg.inc.sync.aligned.u32 240;");
    const int wg = (warp >> 2) - 1, w = warp & 3, tid = threadIdx.x & 127;
    Cons r; r.base = sbase; r.full0 = full0; r.it = 0; r.lane = lane;
    uint32_t qf[48];
    STAMP(0, 0);
    for (uint32_t n = 0;; n++) {
      int task;
      mbar_wait(tfull0 + 8 * (n & 3), (n >> 2) & 1);
      asm volatile("ld.shared.b32 %0, [%1];" : "=r"(task) : "r"(tbox + 4 * (n & 3)) : "memory");
      task = __shfl_sync(0xffffffffu, task, 0);
      if (lane == 0) mbar_arrive(tempty0 + 8 * (n & 3));
      if (task < 0) break;
      const int type = task & 3, bsel = (task >> 2) & 1, pr = (task >> 3) & 3, h = (task >> 5) & 31, blk = (task >> 10) & 1;
      const int b = pr * 2 + bsel;
      bool valid;
      int row8;
      if (type != 2) {
        qproj(r, qf, park, type == 0, wg, tid);
        if (wg == 1 && type == 0) asm volatile("bar.arrive 1, 256;" ::: "memory");
        valid = (wg == 0 || w < 2);
        row8 = wg * 8 + w * 2;
      } else {
        if (wg == 0) {
          asm volatile("bar.sync 1, 256;" ::: "memory");
#pragma unroll
          for (int ks = 0; ks < 12; ks++)
            asm volatile("ld.shared.v4.b32 {%0, %1, %2, %3}, [%4];" : "=r"(qf[4 * ks]), "=r"(qf[4 * ks + 1]), "=r"(qf[4 * ks + 2]), "=r"(qf[4 * ks + 3]) : "r"(park + (ks * 128 + tid) * 16) : "memory");
        }
        valid = (wg == 0 || w >= 2);
        row8 = wg == 0 ? 4 + w * 2 : (w - 2) * 2;
      }
      uint32_t* st = reinterpret_cast<uint32_t*>(g_stash) + (size_t)((blk * NH + h) * NB + b) * 9216 + row8 * 256;
      attention(r, qf, valid, st, sig0 + 8 * (n & 3), wg);
      STAMP(n + 1, task);
    }
  }
}

constexpr int NS2 = 9;
constexpr int SMEM2_BYTES = NS2 * SLOT + 1024 + 256;
constexpr int AX = N_OD - 20;
#define AE 20
#define B5 0
#define CHB4 0, 8, 16, 24, 32
#define CHB5 0, 7, 13, 19, 25, 32
constexpr int N_CTA2 = N_OD + (20 - AX) + 80 + B5;
static_assert(AX >= 0 && AX <= 20 && N_CTA2 <= 140, "bad O-projection table");

__global__ void __launch_bounds__(384, 1) oproj_kernel(const __grid_constant__ Maps maps, __nv_bfloat16* out) {
  extern __shared__ uint8_t smem_raw[];
  const uint32_t sbase = (smem_u32(smem_raw) + 1023u) & ~1023u;
  const uint32_t full0 = sbase + NS2 * SLOT, empty0 = full0 + 8 * NS2;
  const int warp = __shfl_sync(0xffffffffu, threadIdx.x >> 5, 0), lane = threadIdx.x & 31;
  const uint32_t ent = maps.otab[blockIdx.x];
  const int blk = ent & 1, tl = (ent >> 1) & 31, h0 = (ent >> 6) & 63, nh = (ent >> 12) & 63;
  const unsigned int nch = (ent >> 18) & 15;
  const bool fin = (ent >> 22) & 1;
  const int pr = tl & 3, nt = tl >> 2;
  if (threadIdx.x == 0) {
    for (int i = 0; i < NS2; i++) { mbar_init(full0 + 8 * i, 1); mbar_init(empty0 + 8 * i, 8); }
    asm volatile("prefetch.tensormap [%0];" :: "l"(&maps.wo[blk]) : "memory");
    asm volatile("fence.mbarrier_init.release.cluster;" ::: "memory");
  }
  uint32_t par;
  asm volatile("ld.relaxed.gpu.global.u32 %0, [%1];" : "=r"(par) : "l"(&g_epoch) : "memory");
  __syncthreads();

  if (warp < 4) {
    if (warp == 0) {
      uint32_t s = 0, ph = 1;
      const uint8_t* src = reinterpret_cast<const uint8_t*>(g_stash) + (size_t)((blk * NH + h0) * NB + pr * 2) * 36864;
      const unsigned int* fl = &g_flag[(blk * NB + pr * 2 + (lane >> 4)) * NH + h0 + (lane & 15)];
      unsigned int ready = 0;
#pragma unroll 1
      for (int hh = 0; hh < nh; hh++) {
        const int krow = (h0 + hh) * DH;
#pragma unroll 1
        for (int q = 0; q < 5; q++) {
          if (q == 1 && hh == 16) ready = 0;
          if (q == 1 && !((ready >> (hh & 15)) & 1)) {
            const bool watch = (hh & 16) + (lane & 15) < nh;
            for (int spin = 0; spin < (1 << 22); spin++) {
              const unsigned int m = __ballot_sync(0xffffffffu, !watch || ld_acquire(fl + (hh & 16)) == 6u);
              ready = m & (m >> 16);
              if ((ready >> (hh & 15)) & 1) break;
              __nanosleep(32);
            }
            asm volatile("fence.proxy.async;" ::: "memory");
          }
          if (lane == 0) {
            mbar_wait(empty0 + 8 * s, ph);
            mbar_expect_tx(full0 + 8 * s, SLOT);
            const uint32_t dst = sbase + s * SLOT, bar = full0 + 8 * s;
            if (q == 0 || q == 3) {
              tma_3d(dst, &maps.wo[blk], 0, krow + (q ? 96 : 0), nt * 2, bar);
            } else {
              const int kc = q == 4 ? 2 : q - 1;
              bulk_load(dst, src + kc * 12288, 12288, bar);
              bulk_load(dst + 12288, src + 36864 + kc * 12288, 12288, bar);
            }
          }
          __syncwarp();
          if (++s == NS2) { s = 0; ph ^= 1; }
        }
        src += NB * 36864;
      }
      if (fin && lane == 0) {
        const int tile = (blk * 4 + pr) * 5 + nt;
        for (int spin = 0; spin < (1 << 22) && ld_acquire(&g_tile_cnt[tile]) != (nch - 1) * 8; spin++) __nanosleep(32);
        g_tile_cnt[tile] = 0;
        asm volatile("fence.proxy.async;" ::: "memory");
        const uint8_t* ps = reinterpret_cast<const uint8_t*>(g_part[par]) + (size_t)tile * 4 * SLOT;
#pragma unroll 1
        for (int q = 0; q < 4; q++) {
          mbar_wait(empty0 + 8 * s, ph);
          mbar_expect_tx(full0 + 8 * s, SLOT);
          bulk_load(sbase + s * SLOT, ps + q * SLOT, SLOT, full0 + 8 * s);
          if (++s == NS2) { s = 0; ph ^= 1; }
        }
      }
      __syncwarp();
      asm volatile("griddepcontrol.wait;" ::: "memory");
      unsigned int d = 0;
      if (lane == 0) d = atomicAdd(&g_done2, 1u);
      if (__shfl_sync(0xffffffffu, d, 0) == gridDim.x - 1) {
        for (int i = lane; i < 2 * NB * NH; i += 32) g_flag[i] = 0;
        if (lane == 0) { g_done2 = 0; g_epoch = par ^ 1; }
      }
    }
  } else {
    const int wg = (warp >> 2) - 1, w = warp & 3, tid = threadIdx.x & 127;
    uint32_t s = 0, ph = 0;
    auto next = [&](uint32_t& slot) -> uint32_t {
      slot = s;
      mbar_wait(full0 + 8 * s, ph);
      if (++s == NS2) { s = 0; ph ^= 1; }
      return sbase + slot * SLOT;
    };
    auto release = [&](uint32_t slot) { if (lane == 0) mbar_arrive(empty0 + 8 * slot); };
    const int tile = (blk * 4 + pr) * 5 + nt;
    float acc[96];
    uint32_t pw1 = 0, po2 = 0;
    for (int hh = 0; hh < nh; hh++) {
      uint32_t sw0, so0, so1, sw1, so2;
      const uint64_t dw0 = desc_mnmajor_sw128<1024>(next(sw0) + wg * 12288);
      const uint64_t do0 = desc_kmajor_nosw(next(so0));
      wg_fence();
#pragma unroll
      for (int ks = 0; ks < 4; ks++) wgmma_st_n192_t0(acc, dw0 + ks * 128, do0 + ks * 16, (hh > 0 || ks > 0) ? 1 : 0);
      wg_commit();
      if (hh > 0) { wg_wait<1>(); release(pw1); release(po2); }
      else asm volatile("and.b32 %0, %0, 1;" : "+r"(par));
      const uint64_t do1 = desc_kmajor_nosw(next(so1));
      const uint64_t dw1 = desc_mnmajor_sw128<1024>(next(sw1) + wg * 12288);
      wg_fence();
      wgmma_st_n192_t0(acc, dw0 + 4 * 128, do1, 1);
      wgmma_st_n192_t0(acc, dw0 + 5 * 128, do1 + 16, 1);
      wgmma_st_n192_t0(acc, dw1, do1 + 32, 1);
      wgmma_st_n192_t0(acc, dw1 + 128, do1 + 48, 1);
      wg_commit();
      wg_wait<1>(); release(so0);
      const uint64_t do2 = desc_kmajor_nosw(next(so2));
      wg_fence();
#pragma unroll
      for (int ks = 0; ks < 4; ks++) wgmma_st_n192_t0(acc, dw1 + (2 + ks) * 128, do2 + ks * 16, 1);
      wg_commit();
      wg_wait<1>(); release(sw0); release(so1);
      pw1 = sw1; po2 = so2;
    }
    wg_wait<0>();
    touch(acc);
    float4* part = g_part[par] + (size_t)(tile * 2 + wg) * 24 * 128 + tid;
    if (!fin) {
#pragma unroll
      for (int j = 0; j < 24; j++)
        asm volatile("red.global.add.v4.f32 [%0], {%1, %2, %3, %4};" :: "l"(part + j * 128), "f"(acc[4 * j]), "f"(acc[4 * j + 1]), "f"(acc[4 * j + 2]), "f"(acc[4 * j + 3]) : "memory");
      __threadfence();
      __syncwarp();
      if (lane == 0) atomicAdd(&g_tile_cnt[tile], 1u);
      for (int i = (int)(ent >> 23) * 256 + (int)threadIdx.x - 128; i < 40 * 2 * 24 * 128; i += (N_CTA2 - 40) * 256)
        __stcg(g_part[par ^ 1] + i, make_float4(0.f, 0.f, 0.f, 0.f));
    } else {
      release(pw1); release(po2);
      asm volatile("bar.sync 3, 256;" ::: "memory");
      uint32_t sl, pa[4];
#pragma unroll
      for (int q = 0; q < 4; q++) {
        pa[q] = sbase + s * SLOT;
        if ((q >> 1) == wg) next(sl); else if (++s == NS2) { s = 0; ph ^= 1; }
      }
      const uint32_t s1 = s + 1 == NS2 ? 0 : s + 1;
      const uint32_t stg = sbase + (wg ? s1 : s) * SLOT;
      const int q = lane & 3;
      const bool odd = (lane >> 2) & 1;
      const int r8 = 2 * q + (odd ? 1 : 0);
      const uint32_t w0a = stg + r8 * 128 + (((2 * w) ^ r8) << 4) + (lane >> 3) * 4, w1a = stg + r8 * 128 + (((2 * w + 1) ^ r8) << 4) + (lane >> 3) * 4;
      const uint32_t p0 = (wg ? pa[2] : pa[0]) + tid * 16, p1 = (wg ? pa[3] : pa[1]) + tid * 16;
#pragma unroll
      for (int j = 0; j < 24; j++) {
        float4 e;
        asm volatile("ld.shared.v4.f32 {%0, %1, %2, %3}, [%4];" : "=f"(e.x), "=f"(e.y), "=f"(e.z), "=f"(e.w) : "r"((j < 12 ? p0 : p1) + (j % 12) * 2048) : "memory");
        const float x = acc[4 * j] + e.x, y = acc[4 * j + 1] + e.y, z = acc[4 * j + 2] + e.z, u = acc[4 * j + 3] + e.w;
        const float rx = __shfl_xor_sync(0xffffffffu, odd ? x : y, 4), rz = __shfl_xor_sync(0xffffffffu, odd ? z : u, 4);
        asm volatile("st.shared.b32 [%0], %1;" :: "r"(w0a + j * 1024), "r"(odd ? pack_bf16(rx, y) : pack_bf16(x, rx)) : "memory");
        asm volatile("st.shared.b32 [%0], %1;" :: "r"(w1a + j * 1024), "r"(odd ? pack_bf16(rz, u) : pack_bf16(z, rz)) : "memory");
      }
      asm volatile("bar.sync %0, 128;" :: "r"(1 + wg) : "memory");
      uint8_t* ob = reinterpret_cast<uint8_t*>(out + (size_t)(pr * 192) * (2 * DM) + blk * DM + nt * 128 + wg * 64);
#pragma unroll
      for (int i = 0; i < 12; i++) {
        const int row = i * 16 + (tid >> 3), ck = tid & 7;
        uint4 v;
        asm volatile("ld.shared.v4.b32 {%0, %1, %2, %3}, [%4];" : "=r"(v.x), "=r"(v.y), "=r"(v.z), "=r"(v.w) : "r"(stg + row * 128 + ((ck ^ (row & 7)) << 4)) : "memory");
        *reinterpret_cast<uint4*>(ob + (size_t)row * (4 * DM) + ck * 16) = v;
      }
    }
  }
}

typedef CUresult (*EncodeFn)(CUtensorMap*, CUtensorMapDataType, cuuint32_t, void*, const cuuint64_t*, const cuuint64_t*, const cuuint32_t*, const cuuint32_t*,
                             CUtensorMapInterleave, CUtensorMapSwizzle, CUtensorMapL2promotion, CUtensorMapFloatOOBfill);

void make_map(EncodeFn fn, CUtensorMap* m, const void* ptr, int rank, const uint64_t* dims, const uint64_t* strides, const uint32_t* box) {
  cuuint32_t es[4] = {1, 1, 1, 1};
  fn(m, CU_TENSOR_MAP_DATA_TYPE_BFLOAT16, rank, const_cast<void*>(ptr), dims, strides, box, es, CU_TENSOR_MAP_INTERLEAVE_NONE,
     CU_TENSOR_MAP_SWIZZLE_128B, L2PROMO, CU_TENSOR_MAP_FLOAT_OOB_FILL_NONE);
}

}

extern "C" void kernel_launch(void* const* d_in, const int* in_sizes, int n_in, void* d_out, int out_size) {
  static Maps maps;
  static const void* cached[10] = {nullptr};
  static bool init = false;
  static int grid = NCTA;
  bool same = init;
  for (int i = 0; i < 10; i++) same = same && (cached[i] == d_in[i]);
  if (!same) {
    void* fnp = nullptr;
    cudaDriverEntryPointQueryResult qr;
    cudaGetDriverEntryPoint("cuTensorMapEncodeTiled", &fnp, cudaEnableDefault, &qr);
    EncodeFn fn = (EncodeFn)fnp;
    for (int b = 0; b < 2; b++) {
      const void* x = d_in[5 * b + 0]; const void* k = d_in[5 * b + 1]; const void* v = d_in[5 * b + 2];
      const void* wq = d_in[5 * b + 3]; const void* wo = d_in[5 * b + 4];
      { uint64_t d[2] = {DM, NB * SQ}; uint64_t s[1] = {DM * 2}; uint32_t bx[2] = {64, 192}; make_map(fn, &maps.x[b], x, 2, d, s, bx);
        uint32_t b1[2] = {64, 96}; make_map(fn, &maps.x1[b], x, 2, d, s, b1); }
      { uint64_t d[4] = {64, 8, NH * DH / 64, DM / 8}; uint64_t s[3] = {NH * DH * 2, 128, 8 * NH * DH * 2}; uint32_t bx[4] = {64, 8, 3, 8}; make_map(fn, &maps.wq[b], wq, 4, d, s, bx); }
      { uint64_t d[4] = {64, 8, 3, (uint64_t)NB * NH * SK / 8}; uint64_t s[3] = {DH * 2, 128, 8 * DH * 2}; uint32_t bx[4] = {64, 8, 3, 8};
        make_map(fn, &maps.k[b], k, 4, d, s, bx); make_map(fn, &maps.v[b], v, 4, d, s, bx); }
      { uint64_t d[3] = {64, NH * DH, DM / 64}; uint64_t s[2] = {DM * 2, 128}; uint32_t bx[3] = {64, 96, 2}; make_map(fn, &maps.wo[b], wo, 3, d, s, bx); }
    }
    {
      const int b4[5] = {CHB4}, b5[6] = {CHB5};
      int n = 0, nz = 0;
      auto add = [&](int blk, int tl, int h0, int h1, int nch) { maps.otab[n++] = blk | (tl << 1) | (h0 << 6) | ((h1 - h0) << 12) | (nch << 18) | ((h1 == NH) << 22) | ((h1 == NH ? 0u : (unsigned)nz++) << 23); };
      for (int tl = 0; tl < 20; tl++) add(0, tl, 0, tl < AX ? 16 : AE, 2);
      for (int tl = 0; tl < 20; tl++) add(0, tl, tl < AX ? 16 : AE, 32, 2);
      for (int c = 0; c < 5; c++)
        for (int tl = 19; tl >= 0; tl--) {
          if (tl < B5) add(1, tl, b5[c], b5[c + 1], 5);
          else if (c < 3) add(1, tl, b4[c], b4[c + 1], 4);
          else if (c == 4) add(1, tl, b4[3], b4[4], 4);
        }
    }
    cudaFuncSetAttribute(attn_kernel, cudaFuncAttributeMaxDynamicSharedMemorySize, SMEM_BYTES);
    cudaFuncSetAttribute(oproj_kernel, cudaFuncAttributeMaxDynamicSharedMemorySize, SMEM2_BYTES);
    int dev = 0, sms = NCTA;
    cudaGetDevice(&dev);
    cudaDeviceGetAttribute(&sms, cudaDevAttrMultiProcessorCount, dev);
    grid = sms < NCTA ? sms : NCTA;
    for (int i = 0; i < 10; i++) cached[i] = d_in[i];
    init = true;
  }
  attn_kernel<<<grid, 384, SMEM_BYTES>>>(maps);
  cudaLaunchConfig_t cfg = {};
  cfg.gridDim = dim3(N_CTA2); cfg.blockDim = dim3(384); cfg.dynamicSmemBytes = SMEM2_BYTES; cfg.stream = cudaStreamPerThread;
  cudaLaunchAttribute at[1];
  at[0].id = cudaLaunchAttributeProgrammaticStreamSerialization; at[0].val.programmaticStreamSerializationAllowed = PDL;
  cfg.attrs = at; cfg.numAttrs = 1;
  cudaLaunchKernelEx(&cfg, oproj_kernel, maps, (__nv_bfloat16*)d_out);
}
```

```cpp
#include <cuda_runtime.h>
#include <cuda_bf16.h>
#include <cuda.h>
#include <stdint.h>

namespace {

constexpr int NB = 8, SQ = 96, DM = 640, NH = 32, SK = 512, DH = 192;
constexpr int SLOT = 24576;
constexpr int NSLOT = 8;
constexpr int SMEM_BYTES = NSLOT * SLOT + SLOT   + 1024   + 256  ;

#define NCTA 132
#define N_ATT 66
#define NPAIR 208
#define FETCH_AHEAD 3
#define KV_INFLIGHT 8
#define WQ_EF 2
#define N_OD 20
#define L2PROMO CU_TENSOR_MAP_L2_PROMOTION_NONE
#define KVPOL 0
#define PDL 1
constexpr int N_TICKETS = NPAIR + 2 * (256 - NPAIR) + (NCTA - N_ATT) / 2;

struct Maps { CUtensorMap x[2], x1[2], wq[2], k[2], v[2], wo[2]; uint32_t otab[140]; };

__device__ uint4 g_stash[2 * NH * NB * 2304];
__device__ float4 g_part[2][40 * 2 * 24 * 128];
__device__ unsigned int g_epoch;
__device__ unsigned int g_tile_cnt[40];
__device__ unsigned int g_flag[2 * NB * NH];
__device__ unsigned int g_ticket, g_done, g_done2;

#define STAMP(i, tk)

__device__ __forceinline__ uint32_t smem_u32(const void* p) { return (uint32_t)__cvta_generic_to_shared(p); }
__device__ __forceinline__ void mbar_init(uint32_t bar, int cnt) { asm volatile("mbarrier.init.shared::cta.b64 [%0], %1;" :: "r"(bar), "r"(cnt) : "memory"); }
__device__ __forceinline__ void mbar_expect_tx(uint32_t bar, uint32_t bytes) { asm volatile("mbarrier.arrive.expect_tx.shared::cta.b64 _, [%0], %1;" :: "r"(bar), "r"(bytes) : "memory"); }
__device__ __forceinline__ void mbar_arrive(uint32_t bar) { asm volatile("mbarrier.arrive.shared::cta.b64 _, [%0];" :: "r"(bar) : "memory"); }
__device__ __forceinline__ void mbar_wait(uint32_t bar, uint32_t parity) {
  asm volatile("{\n.reg .pred p;\nWAIT_%=:\nmbarrier.try_wait.parity.shared::cta.b64 p, [%0], %1;\n@p bra DONE_%=;\nbra WAIT_%=;\nDONE_%=:\n}" :: "r"(bar), "r"(parity) : "memory");
}
__device__ __forceinline__ void tma_2d(uint32_t dst, const CUtensorMap* m, int c0, int c1, uint32_t bar) {
  asm volatile("cp.async.bulk.tensor.2d.shared::cluster.global.mbarrier::complete_tx::bytes [%0], [%1, {%3, %4}], [%2];"
               :: "r"(dst), "l"(m), "r"(bar), "r"(c0), "r"(c1) : "memory");
}
__device__ __forceinline__ void tma_3d(uint32_t dst, const CUtensorMap* m, int c0, int c1, int c2, uint32_t bar) {
  asm volatile("cp.async.bulk.tensor.3d.shared::cluster.global.mbarrier::complete_tx::bytes [%0], [%1, {%3, %4, %5}], [%2];"
               :: "r"(dst), "l"(m), "r"(bar), "r"(c0), "r"(c1), "r"(c2) : "memory");
}
__device__ __forceinline__ void tma_4d(uint32_t dst, const CUtensorMap* m, int c2, int c3, uint32_t bar) {
  asm volatile("cp.async.bulk.tensor.4d.shared::cluster.global.mbarrier::complete_tx::bytes [%0], [%1, {%3, %3, %4, %5}], [%2];"
               :: "r"(dst), "l"(m), "r"(bar), "r"(0), "r"(c2), "r"(c3) : "memory");
}
__device__ __forceinline__ void tma_4d_hint(uint32_t dst, const CUtensorMap* m, int c2, int c3, uint32_t bar, uint64_t pol) {
  asm volatile("cp.async.bulk.tensor.4d.shared::cluster.global.mbarrier::complete_tx::bytes.L2::cache_hint [%0], [%1, {%3, %3, %4, %5}], [%2], %6;"
               :: "r"(dst), "l"(m), "r"(bar), "r"(0), "r"(c2), "r"(c3), "l"(pol) : "memory");
}
__device__ __forceinline__ void bulk_load(uint32_t dst, const void* src, uint32_t bytes, uint32_t bar) {
  asm volatile("cp.async.bulk.shared::cluster.global.mbarrier::complete_tx::bytes [%0], [%1], %2, [%3];" :: "r"(dst), "l"(src), "r"(bytes), "r"(bar) : "memory");
}
__device__ __forceinline__ void wg_fence() { asm volatile("wgmma.fence.sync.aligned;" ::: "memory"); }
__device__ __forceinline__ void wg_commit() { asm volatile("wgmma.commit_group.sync.aligned;" ::: "memory"); }
template <int N> __device__ __forceinline__ void wg_wait() { asm volatile("wgmma.wait_group.sync.aligned %0;" :: "n"(N) : "memory"); }
template <int N> __device__ __forceinline__ void touch(float (&d)[N]) {
#pragma unroll
  for (int i = 0; i < N; i++) asm volatile("" : "+f"(d[i]) :: "memory");
}
template <int N> __device__ __forceinline__ void touch_u(uint32_t (&d)[N]) {
#pragma unroll
  for (int i = 0; i < N; i++) asm volatile("" : "+r"(d[i]) :: "memory");
}
__device__ __forceinline__ float ex2(float x) { float y; asm("ex2.approx.ftz.f32 %0, %1;" : "=f"(y) : "f"(x)); return y; }
__device__ __forceinline__ uint32_t pack_bf16(float lo, float hi) { uint32_t r; asm("cvt.rn.bf16x2.f32 %0, %1, %2;" : "=r"(r) : "f"(hi), "f"(lo)); return r; }

constexpr uint64_t DESC_SW128 = (uint64_t)1 << 62;
__device__ __forceinline__ uint64_t desc_kmajor_sw128(uint32_t addr) {
  return DESC_SW128 | ((uint64_t)(1024 >> 4) << 32) | ((uint64_t)1 << 16) | (uint64_t)((addr & 0x3FFFF) >> 4);
}
__device__ __forceinline__ uint64_t desc_k_il(uint32_t addr) {
  return DESC_SW128 | ((uint64_t)(3072 >> 4) << 32) | ((uint64_t)1 << 16) | (uint64_t)((addr & 0x3FFFF) >> 4);
}
__device__ __forceinline__ uint64_t desc_mn_il(uint32_t addr) {
  return DESC_SW128 | ((uint64_t)(3072 >> 4) << 32) | ((uint64_t)(1024 >> 4) << 16) | (uint64_t)((addr & 0x3FFFF) >> 4);
}
template <int LBO> __device__ __forceinline__ uint64_t desc_mnmajor_sw128(uint32_t addr) {
  return DESC_SW128 | ((uint64_t)(1024 >> 4) << 32) | ((uint64_t)(LBO >> 4) << 16) | (uint64_t)((addr & 0x3FFFF) >> 4);
}
__device__ __forceinline__ uint64_t desc_kmajor_nosw(uint32_t addr) {
  return ((uint64_t)(1024 >> 4) << 32) | ((uint64_t)(128 >> 4) << 16) | (uint64_t)((addr & 0x3FFFF) >> 4);
}

__device__ __forceinline__ void wgmma_rs_n64_t0(float (&d)[32], uint32_t a0, uint32_t a1, uint32_t a2, uint32_t a3, uint64_t descB, int scaleD) {
  asm volatile("{\n.reg .pred p;\nsetp.ne.b32 p, %37, 0;\n"
    "wgmma.mma_async.sync.aligned.m64n64k16.f32.bf16.bf16 "
    "{%0, %1, %2, %3, %4, %5, %6, %7, %8, %9, %10, %11, %12, %13, %14, %15, %16, %17, %18, %19, %20, %21, %22, %23, %24, %25, %26, %27, %28, %29, %30, %31}, "
    "{%32, %33, %34, %35}, %36, p, 1, 1, 0;\n}\n"
    : "+f"(d[0]), "+f"(d[1]), "+f"(d[2]), "+f"(d[3]), "+f"(d[4]), "+f"(d[5]), "+f"(d[6]), "+f"(d[7]), "+f"(d[8]), "+f"(d[9]), "+f"(d[10]), "+f"(d[11]), "+f"(d[12]), "+f"(d[13]), "+f"(d[14]), "+f"(d[15]), "+f"(d[16]), "+f"(d[17]), "+f"(d[18]), "+f"(d[19]), "+f"(d[20]), "+f"(d[21]), "+f"(d[22]), "+f"(d[23]), "+f"(d[24]), "+f"(d[25]), "+f"(d[26]), "+f"(d[27]), "+f"(d[28]), "+f"(d[29]), "+f"(d[30]), "+f"(d[31])
    : "r"(a0), "r"(a1), "r"(a2), "r"(a3), "l"(descB), "r"(scaleD));
}
__device__ __forceinline__ void wgmma_rs_n192_t1(float (&d)[96], uint32_t a0, uint32_t a1, uint32_t a2, uint32_t a3, uint64_t descB, int scaleD) {
  asm volatile("{\n.reg .pred p;\nsetp.ne.b32 p, %101, 0;\n"
    "wgmma.mma_async.sync.aligned.m64n192k16.f32.bf16.bf16 "
    "{%0, %1, %2, %3, %4, %5, %6, %7, %8, %9, %10, %11, %12, %13, %14, %15, %16, %17, %18, %19, %20, %21, %22, %23, %24, %25, %26, %27, %28, %29, %30, %31, %32, %33, %34, %35, %36, %37, %38, %39, %40, %41, %42, %43, %44, %45, %46, %47, %48, %49, %50, %51, %52, %53, %54, %55, %56, %57, %58, %59, %60, %61, %62, %63, %64, %65, %66, %67, %68, %69, %70, %71, %72, %73, %74, %75, %76, %77, %78, %79, %80, %81, %82, %83, %84, %85, %86, %87, %88, %89, %90, %91, %92, %93, %94, %95}, "
    "{%96, %97, %98, %99}, %100, p, 1, 1, 1;\n}\n"
    : "+f"(d[0]), "+f"(d[1]), "+f"(d[2]), "+f"(d[3]), "+f"(d[4]), "+f"(d[5]), "+f"(d[6]), "+f"(d[7]), "+f"(d[8]), "+f"(d[9]), "+f"(d[10]), "+f"(d[11]), "+f"(d[12]), "+f"(d[13]), "+f"(d[14]), "+f"(d[15]), "+f"(d[16]), "+f"(d[17]), "+f"(d[18]), "+f"(d[19]), "+f"(d[20]), "+f"(d[21]), "+f"(d[22]), "+f"(d[23]), "+f"(d[24]), "+f"(d[25]), "+f"(d[26]), "+f"(d[27]), "+f"(d[28]), "+f"(d[29]), "+f"(d[30]), "+f"(d[31]), "+f"(d[32]), "+f"(d[33]), "+f"(d[34]), "+f"(d[35]), "+f"(d[36]), "+f"(d[37]), "+f"(d[38]), "+f"(d[39]), "+f"(d[40]), "+f"(d[41]), "+f"(d[42]), "+f"(d[43]), "+f"(d[44]), "+f"(d[45]), "+f"(d[46]), "+f"(d[47]), "+f"(d[48]), "+f"(d[49]), "+f"(d[50]), "+f"(d[51]), "+f"(d[52]), "+f"(d[53]), "+f"(d[54]), "+f"(d[55]), "+f"(d[56]), "+f"(d[57]), "+f"(d[58]), "+f"(d[59]), "+f"(d[60]), "+f"(d[61]), "+f"(d[62]), "+f"(d[63]), "+f"(d[64]), "+f"(d[65]), "+f"(d[66]), "+f"(d[67]), "+f"(d[68]), "+f"(d[69]), "+f"(d[70]), "+f"(d[71]), "+f"(d[72]), "+f"(d[73]), "+f"(d[74]), "+f"(d[75]), "+f"(d[76]), "+f"(d[77]), "+f"(d[78]), "+f"(d[79]), "+f"(d[80]), "+f"(d[81]), "+f"(d[82]), "+f"(d[83]), "+f"(d[84]), "+f"(d[85]), "+f"(d[86]), "+f"(d[87]), "+f"(d[88]), "+f"(d[89]), "+f"(d[90]), "+f"(d[91]), "+f"(d[92]), "+f"(d[93]), "+f"(d[94]), "+f"(d[95])
    : "r"(a0), "r"(a1), "r"(a2), "r"(a3), "l"(descB), "r"(scaleD));
}
__device__ __forceinline__ void wgmma_ss_n192_t1(float (&d)[96], uint64_t descA, uint64_t descB, int scaleD) {
  asm volatile("{\n.reg .pred p;\nsetp.ne.b32 p, %98, 0;\n"
    "wgmma.mma_async.sync.aligned.m64n192k16.f32.bf16.bf16 "
    "{%0, %1, %2, %3, %4, %5, %6, %7, %8, %9, %10, %11, %12, %13, %14, %15, %16, %17, %18, %19, %20, %21, %22, %23, %24, %25, %26, %27, %28, %29, %30, %31, %32, %33, %34, %35, %36, %37, %38, %39, %40, %41, %42, %43, %44, %45, %46, %47, %48, %49, %50, %51, %52, %53, %54, %55, %56, %57, %58, %59, %60, %61, %62, %63, %64, %65, %66, %67, %68, %69, %70, %71, %72, %73, %74, %75, %76, %77, %78, %79, %80, %81, %82, %83, %84, %85, %86, %87, %88, %89, %90, %91, %92, %93, %94, %95}, "
    "%96, %97, p, 1, 1, 0, 1;\n}\n"
    : "+f"(d[0]), "+f"(d[1]), "+f"(d[2]), "+f"(d[3]), "+f"(d[4]), "+f"(d[5]), "+f"(d[6]), "+f"(d[7]), "+f"(d[8]), "+f"(d[9]), "+f"(d[10]), "+f"(d[11]), "+f"(d[12]), "+f"(d[13]), "+f"(d[14]), "+f"(d[15]), "+f"(d[16]), "+f"(d[17]), "+f"(d[18]), "+f"(d[19]), "+f"(d[20]), "+f"(d[21]), "+f"(d[22]), "+f"(d[23]), "+f"(d[24]), "+f"(d[25]), "+f"(d[26]), "+f"(d[27]), "+f"(d[28]), "+f"(d[29]), "+f"(d[30]), "+f"(d[31]), "+f"(d[32]), "+f"(d[33]), "+f"(d[34]), "+f"(d[35]), "+f"(d[36]), "+f"(d[37]), "+f"(d[38]), "+f"(d[39]), "+f"(d[40]), "+f"(d[41]), "+f"(d[42]), "+f"(d[43]), "+f"(d[44]), "+f"(d[45]), "+f"(d[46]), "+f"(d[47]), "+f"(d[48]), "+f"(d[49]), "+f"(d[50]), "+f"(d[51]), "+f"(d[52]), "+f"(d[53]), "+f"(d[54]), "+f"(d[55]), "+f"(d[56]), "+f"(d[57]), "+f"(d[58]), "+f"(d[59]), "+f"(d[60]), "+f"(d[61]), "+f"(d[62]), "+f"(d[63]), "+f"(d[64]), "+f"(d[65]), "+f"(d[66]), "+f"(d[67]), "+f"(d[68]), "+f"(d[69]), "+f"(d[70]), "+f"(d[71]), "+f"(d[72]), "+f"(d[73]), "+f"(d[74]), "+f"(d[75]), "+f"(d[76]), "+f"(d[77]), "+f"(d[78]), "+f"(d[79]), "+f"(d[80]), "+f"(d[81]), "+f"(d[82]), "+f"(d[83]), "+f"(d[84]), "+f"(d[85]), "+f"(d[86]), "+f"(d[87]), "+f"(d[88]), "+f"(d[89]), "+f"(d[90]), "+f"(d[91]), "+f"(d[92]), "+f"(d[93]), "+f"(d[94]), "+f"(d[95])
    : "l"(descA), "l"(descB), "r"(scaleD));
}
__device__ __forceinline__ void wgmma_ss_n64_t1(float (&d)[32], uint64_t descA, uint64_t descB, int scaleD) {
  asm volatile("{\n.reg .pred p;\nsetp.ne.b32 p, %34, 0;\n"
    "wgmma.mma_async.sync.aligned.m64n64k16.f32.bf16.bf16 "
    "{%0, %1, %2, %3, %4, %5, %6, %7, %8, %9, %10, %11, %12, %13, %14, %15, %16, %17, %18, %19, %20, %21, %22, %23, %24, %25, %26, %27, %28, %29, %30, %31}, "
    "%32, %33, p, 1, 1, 0, 1;\n}\n"
    : "+f"(d[0]), "+f"(d[1]), "+f"(d[2]), "+f"(d[3]), "+f"(d[4]), "+f"(d[5]), "+f"(d[6]), "+f"(d[7]), "+f"(d[8]), "+f"(d[9]), "+f"(d[10]), "+f"(d[11]), "+f"(d[12]), "+f"(d[13]), "+f"(d[14]), "+f"(d[15]), "+f"(d[16]), "+f"(d[17]), "+f"(d[18]), "+f"(d[19]), "+f"(d[20]), "+f"(d[21]), "+f"(d[22]), "+f"(d[23]), "+f"(d[24]), "+f"(d[25]), "+f"(d[26]), "+f"(d[27]), "+f"(d[28]), "+f"(d[29]), "+f"(d[30]), "+f"(d[31])
    : "l"(descA), "l"(descB), "r"(scaleD));
}
__device__ __forceinline__ void wgmma_ss_n32_t1(float (&d)[16], uint64_t descA, uint64_t descB, int scaleD) {
  asm volatile("{\n.reg .pred p;\nsetp.ne.b32 p, %18, 0;\n"
    "wgmma.mma_async.sync.aligned.m64n32k16.f32.bf16.bf16 "
    "{%0, %1, %2, %3, %4, %5, %6, %7, %8, %9, %10, %11, %12, %13, %14, %15}, "
    "%16, %17, p, 1, 1, 0, 1;\n}\n"
    : "+f"(d[0]), "+f"(d[1]), "+f"(d[2]), "+f"(d[3]), "+f"(d[4]), "+f"(d[5]), "+f"(d[6]), "+f"(d[7]), "+f"(d[8]), "+f"(d[9]), "+f"(d[10]), "+f"(d[11]), "+f"(d[12]), "+f"(d[13]), "+f"(d[14]), "+f"(d[15])
    : "l"(descA), "l"(descB), "r"(scaleD));
}
__device__ __forceinline__ void wgmma_st_n192_t0(float (&d)[96], uint64_t descA, uint64_t descB, int scaleD) {
  asm volatile("{\n.reg .pred p;\nsetp.ne.b32 p, %98, 0;\n"
    "wgmma.mma_async.sync.aligned.m64n192k16.f32.bf16.bf16 "
    "{%0, %1, %2, %3, %4, %5, %6, %7, %8, %9, %10, %11, %12, %13, %14, %15, %16, %17, %18, %19, %20, %21, %22, %23, %24, %25, %26, %27, %28, %29, %30, %31, %32, %33, %34, %35, %36, %37, %38, %39, %40, %41, %42, %43, %44, %45, %46, %47, %48, %49, %50, %51, %52, %53, %54, %55, %56, %57, %58, %59, %60, %61, %62, %63, %64, %65, %66, %67, %68, %69, %70, %71, %72, %73, %74, %75, %76, %77, %78, %79, %80, %81, %82, %83, %84, %85, %86, %87, %88, %89, %90, %91, %92, %93, %94, %95}, "
    "%96, %97, p, 1, 1, 1, 0;\n}\n"
    : "+f"(d[0]), "+f"(d[1]), "+f"(d[2]), "+f"(d[3]), "+f"(d[4]), "+f"(d[5]), "+f"(d[6]), "+f"(d[7]), "+f"(d[8]), "+f"(d[9]), "+f"(d[10]), "+f"(d[11]), "+f"(d[12]), "+f"(d[13]), "+f"(d[14]), "+f"(d[15]), "+f"(d[16]), "+f"(d[17]), "+f"(d[18]), "+f"(d[19]), "+f"(d[20]), "+f"(d[21]), "+f"(d[22]), "+f"(d[23]), "+f"(d[24]), "+f"(d[25]), "+f"(d[26]), "+f"(d[27]), "+f"(d[28]), "+f"(d[29]), "+f"(d[30]), "+f"(d[31]), "+f"(d[32]), "+f"(d[33]), "+f"(d[34]), "+f"(d[35]), "+f"(d[36]), "+f"(d[37]), "+f"(d[38]), "+f"(d[39]), "+f"(d[40]), "+f"(d[41]), "+f"(d[42]), "+f"(d[43]), "+f"(d[44]), "+f"(d[45]), "+f"(d[46]), "+f"(d[47]), "+f"(d[48]), "+f"(d[49]), "+f"(d[50]), "+f"(d[51]), "+f"(d[52]), "+f"(d[53]), "+f"(d[54]), "+f"(d[55]), "+f"(d[56]), "+f"(d[57]), "+f"(d[58]), "+f"(d[59]), "+f"(d[60]), "+f"(d[61]), "+f"(d[62]), "+f"(d[63]), "+f"(d[64]), "+f"(d[65]), "+f"(d[66]), "+f"(d[67]), "+f"(d[68]), "+f"(d[69]), "+f"(d[70]), "+f"(d[71]), "+f"(d[72]), "+f"(d[73]), "+f"(d[74]), "+f"(d[75]), "+f"(d[76]), "+f"(d[77]), "+f"(d[78]), "+f"(d[79]), "+f"(d[80]), "+f"(d[81]), "+f"(d[82]), "+f"(d[83]), "+f"(d[84]), "+f"(d[85]), "+f"(d[86]), "+f"(d[87]), "+f"(d[88]), "+f"(d[89]), "+f"(d[90]), "+f"(d[91]), "+f"(d[92]), "+f"(d[93]), "+f"(d[94]), "+f"(d[95])
    : "l"(descA), "l"(descB), "r"(scaleD));
}

__device__ __forceinline__ unsigned int ld_acquire(const unsigned int* p) { unsigned int v; asm volatile("ld.acquire.gpu.global.u32 %0, [%1];" : "=r"(v) : "l"(p) : "memory"); return v; }

struct Cons {
  uint32_t base, full0;
  uint32_t it;
  int lane;
  __device__ __forceinline__ uint32_t wait(uint32_t slot, uint32_t u) const { mbar_wait(full0 + slot * 8, (u >> 3) & 1); return base + slot * SLOT; }
  __device__ __forceinline__ uint32_t wait(uint32_t u) const { return wait(u & 7, u); }
  __device__ __forceinline__ void release(uint32_t slot) const { if (lane == 0) mbar_arrive(full0 + 64 + (slot & 7) * 8); }
};

__device__ __forceinline__ int ticket_task(int ticket) {
  int u = ticket, f = 0;
  if (ticket >= N_ATT) {
    if (ticket < NCTA) { const int s = ticket - N_ATT; u = N_ATT + (s >> 1); f = 1 | ((s & 1) << 2); }
    else {
      u = ticket - (NCTA - N_ATT) / 2;
      if (u >= NPAIR) { const int s = u - NPAIR; u = NPAIR + (s >> 1); f = 1 | ((s & 1) << 2); }
    }
  }
  const int hh = u & 7, pr = (u >> 3) & 3, g = (u >> 5) & 3, blk = u >> 7;
  return f | (pr << 3) | ((g * 8 + hh) << 5) | (blk << 10);
}

__device__ __forceinline__ void qproj(Cons& r, uint32_t (&qf)[48], uint32_t park, bool pair, int wg, int tid) {
  float acc[96];
  float acx[32];
  float acy[16];
  for (int c = 0; c < 10; c++) {
    const uint32_t sx = r.it;
    const uint32_t xa = r.wait(sx), wa = r.wait(sx + 1);
    const uint64_t da = desc_kmajor_sw128(xa + wg * 8192), d2 = desc_kmajor_sw128(xa + 2 * 8192);
    const uint64_t db = desc_mn_il(wa), dbx = desc_mn_il(wa + wg * 1024), dby = desc_mn_il(wa + 2048 + wg * 64);
    if (pair) {
      wg_fence();
#pragma unroll
      for (int ks = 0; ks < 4; ks++) {
        const int sc = (c > 0 || ks > 0) ? 1 : 0;
        wgmma_ss_n192_t1(acc, da + ks * 2, db + ks * 384, sc);
        wgmma_ss_n64_t1(acx, d2 + ks * 2, dbx + ks * 384, sc);
        wgmma_ss_n32_t1(acy, d2 + ks * 2, dby + ks * 384, sc);
      }
      wg_commit();
    } else {
      wg_fence();
#pragma unroll
      for (int ks = 0; ks < 4; ks++)
        wgmma_ss_n192_t1(acc, da + ks * 2, db + ks * 384, (c > 0 || ks > 0) ? 1 : 0);
      wg_commit();
    }
    if (c > 0) { wg_wait<1>(); r.release((sx + 6) & 7); r.release((sx + 7) & 7); }
    r.it += 2;
  }
  wg_wait<0>();
  touch(acc); touch(acx); touch(acy);
  r.release((r.it + 6) & 7); r.release((r.it + 7) & 7);
  if (pair) {
#pragma unroll
    for (int ks = 0; ks < 4; ks++) {
      uint32_t a0 = pack_bf16(acx[8 * ks + 0], acx[8 * ks + 1]), a1 = pack_bf16(acx[8 * ks + 2], acx[8 * ks + 3]);
      uint32_t a2 = pack_bf16(acx[8 * ks + 4], acx[8 * ks + 5]), a3 = pack_bf16(acx[8 * ks + 6], acx[8 * ks + 7]);
      asm volatile("st.shared.v4.b32 [%0], {%1, %2, %3, %4};" :: "r"(park + ((wg * 4 + ks) * 128 + tid) * 16), "r"(a0), "r"(a1), "r"(a2), "r"(a3) : "memory");
    }
#pragma unroll
    for (int ks = 0; ks < 2; ks++) {
      uint32_t a0 = pack_bf16(acy[8 * ks + 0], acy[8 * ks + 1]), a1 = pack_bf16(acy[8 * ks + 2], acy[8 * ks + 3]);
      uint32_t a2 = pack_bf16(acy[8 * ks + 4], acy[8 * ks + 5]), a3 = pack_bf16(acy[8 * ks + 6], acy[8 * ks + 7]);
      asm volatile("st.shared.v4.b32 [%0], {%1, %2, %3, %4};" :: "r"(park + ((8 + wg * 2 + ks) * 128 + tid) * 16), "r"(a0), "r"(a1), "r"(a2), "r"(a3) : "memory");
    }
  }
#pragma unroll
  for (int i = 0; i < 48; i++) qf[i] = pack_bf16(acc[2 * i], acc[2 * i + 1]);
}

__device__ __forceinline__ void sched_sync(int wg) { asm volatile("bar.sync %0, 256;" :: "r"(2 + wg) : "memory"); }
__device__ __forceinline__ void sched_arrive(int wg) { asm volatile("bar.arrive %0, 256;" :: "r"(3 - wg) : "memory"); }

__device__ __forceinline__ void issue_qk(float (&s)[32], const uint32_t (&qf)[48], uint64_t dk) {
#pragma unroll
  for (int ks = 0; ks < 12; ks++)
    wgmma_rs_n64_t0(s, qf[4 * ks], qf[4 * ks + 1], qf[4 * ks + 2], qf[4 * ks + 3], dk + ((ks >> 2) * 64 + (ks & 3) * 2), ks > 0);
  wg_commit();
}
__device__ __forceinline__ void attention(Cons& r, const uint32_t (&qf)[48], bool valid, uint32_t* dst, uint32_t sig, int wg) {
  constexpr float CS = 0.07216878364870322f * 1.4426950408889634f;
  const int lane = r.lane;
  float o[96];
  float s[32];
  uint32_t pa[8], pb[8];
  float m0 = -INFINITY, m1 = -INFINITY, l0 = 0.f, l1 = 0.f, al0 = 1.f, al1 = 1.f;
  bool resc = false;
#pragma unroll
  for (int i = 0; i < 8; i++) { pa[i] = 0; pb[i] = 0; }

  auto row_max = [&]() {
    float x0 = fmaxf(s[0], s[1]), x1 = fmaxf(s[2], s[3]), y0 = fmaxf(s[4], s[5]), y1 = fmaxf(s[6], s[7]);
#pragma unroll
    for (int i = 2; i < 8; i += 2) {
      x0 = fmaxf(x0, fmaxf(s[4 * i], s[4 * i + 1])); x1 = fmaxf(x1, fmaxf(s[4 * i + 2], s[4 * i + 3]));
      y0 = fmaxf(y0, fmaxf(s[4 * i + 4], s[4 * i + 5])); y1 = fmaxf(y1, fmaxf(s[4 * i + 6], s[4 * i + 7]));
    }
    x0 = fmaxf(x0, y0); x1 = fmaxf(x1, y1);
    x0 = fmaxf(x0, __shfl_xor_sync(0xffffffffu, x0, 1)); x1 = fmaxf(x1, __shfl_xor_sync(0xffffffffu, x1, 1));
    x0 = fmaxf(x0, __shfl_xor_sync(0xffffffffu, x0, 2)); x1 = fmaxf(x1, __shfl_xor_sync(0xffffffffu, x1, 2));
    resc = __any_sync(0xffffffffu, (x0 - m0) * CS > 8.0f || (x1 - m1) * CS > 8.0f);
    if (resc) {
      const float n0 = fmaxf(m0, x0), n1 = fmaxf(m1, x1);
      al0 = ex2((m0 - n0) * CS); al1 = ex2((m1 - n1) * CS);
      m0 = n0; m1 = n1;
      l0 *= al0; l1 *= al1;
    }
  };
  auto exps = [&](uint32_t (&p)[8], int h) {
    const float c0 = m0 * CS, c1 = m1 * CS;
    float t0 = 0.f, t1 = 0.f;
#pragma unroll
    for (int i = 0; i < 4; i++) {
      const int k = 16 * h + 4 * i;
      const float e0 = ex2(fmaf(s[k], CS, -c0)), e1 = ex2(fmaf(s[k + 1], CS, -c0));
      const float e2 = ex2(fmaf(s[k + 2], CS, -c1)), e3 = ex2(fmaf(s[k + 3], CS, -c1));
      t0 += e0 + e1; t1 += e2 + e3;
      p[2 * i] = pack_bf16(e0, e1); p[2 * i + 1] = pack_bf16(e2, e3);
    }
    l0 += t0; l1 += t1;
  };
  auto pv_a = [&](uint64_t dv, int first) {
    wgmma_rs_n192_t1(o, pa[0], pa[1], pa[2], pa[3], dv, first ? 0 : 1);
    wgmma_rs_n192_t1(o, pa[4], pa[5], pa[6], pa[7], dv + 384, 1);
    wg_commit();
  };
  auto pv_b = [&](uint64_t dv) {
    wgmma_rs_n192_t1(o, pb[0], pb[1], pb[2], pb[3], dv + 768, 1);
    wgmma_rs_n192_t1(o, pb[4], pb[5], pb[6], pb[7], dv + 1152, 1);
    wg_commit();
  };

  if (wg == 1) sched_arrive(1);
  {
    const uint32_t sk = r.it & 7;
    const uint64_t dk = desc_k_il(r.wait(sk, r.it));
    sched_sync(wg);
    wg_fence();
    issue_qk(s, qf, dk);
    sched_arrive(wg);
    wg_wait<0>();
    touch(s);
    r.release(sk);
    if (valid) { row_max(); exps(pa, 0); exps(pb, 1); }
  }
  for (int j = 0; j < 7; j++) {
    const uint32_t u = r.it;
    const uint32_t sv = (u + 1) & 7, sk = (u + 2) & 7;
    const uint64_t dk = desc_k_il(r.wait(sk, u + 2));
    const uint64_t dv = desc_mn_il(r.wait(sv, u + 1));
    sched_sync(wg);
    wg_fence();
    issue_qk(s, qf, dk);
    pv_a(dv, j == 0);
    pv_b(dv);
    sched_arrive(wg);
    wg_wait<2>();
    touch(s);
    r.release(sk);
    if (valid) row_max();
    wg_wait<1>();
    touch_u(pa);
    if (valid) exps(pa, 0);
    touch_u(pa);
    wg_wait<0>();
    touch(o); touch_u(pb);
    r.release(sv);
    if (valid) exps(pb, 1);
    if (resc) {
#pragma unroll
      for (int i = 0; i < 24; i++) { o[4 * i] *= al0; o[4 * i + 1] *= al0; o[4 * i + 2] *= al1; o[4 * i + 3] *= al1; }
    }
    touch_u(pb);
    r.it += 2;
  }
  {
    const uint32_t sv = (r.it + 1) & 7;
    const uint64_t dv = desc_mn_il(r.wait(sv, r.it + 1));
    sched_sync(wg);
    wg_fence();
    pv_a(dv, 0);
    pv_b(dv);
    if (wg == 0) sched_arrive(0);
    wg_wait<0>();
    touch(o); touch_u(pa); touch_u(pb);
    r.release(sv);
    r.it += 2;
  }
  if (valid) {
    l0 += __shfl_xor_sync(0xffffffffu, l0, 1); l1 += __shfl_xor_sync(0xffffffffu, l1, 1);
    l0 += __shfl_xor_sync(0xffffffffu, l0, 2); l1 += __shfl_xor_sync(0xffffffffu, l1, 2);
    const float i0 = 1.0f / l0, i1 = 1.0f / l1;
#pragma unroll
    for (int kc = 0; kc < 24; kc++) {
      dst[(kc >> 3) * 3072 + (kc & 7) * 32 + lane] = pack_bf16(o[4 * kc] * i0, o[4 * kc + 1] * i0);
      dst[(kc >> 3) * 3072 + 256 + (kc & 7) * 32 + lane] = pack_bf16(o[4 * kc + 2] * i1, o[4 * kc + 3] * i1);
    }
    __syncwarp();
    if (lane == 0) mbar_arrive(sig);
  }
}

__global__ void __launch_bounds__(384, 1) attn_kernel(const __grid_constant__ Maps maps) {
  extern __shared__ uint8_t smem_raw[];
  const uint32_t sbase = (smem_u32(smem_raw) + 1023u) & ~1023u;
  const uint32_t park = sbase + NSLOT * SLOT;
  const uint32_t bars = park + SLOT;
  const uint32_t full0 = bars, empty0 = bars + 64;
  const uint32_t tfull0 = bars + 128, tempty0 = bars + 160, sig0 = bars + 192, tbox = bars + 224, sreq = bars + 240;
  const int warp = __shfl_sync(0xffffffffu, threadIdx.x >> 5, 0), lane = threadIdx.x & 31;
  if (threadIdx.x == 0) {
    for (int i = 0; i < NSLOT; i++) { mbar_init(full0 + 8 * i, 1); mbar_init(empty0 + 8 * i, 8); }
    for (int i = 0; i < 4; i++) { mbar_init(tfull0 + 8 * i, 1); mbar_init(tempty0 + 8 * i, 10); mbar_init(sig0 + 8 * i, 6); }
    mbar_init(sreq, 1);
    asm volatile("fence.mbarrier_init.release.cluster;" ::: "memory");
  }
  __syncthreads();
  asm volatile("griddepcontrol.launch_dependents;");

  if (warp < 4) {
    asm volatile("setmaxnreg.dec.sync.aligned.u32 24;");
    if (warp == 0 && lane == 0) {
      uint64_t pol;
      asm volatile("createpolicy.fractional.L2::evict_first.b64 %0, 1.0;" : "=l"(pol));
      uint32_t u = 0;
      auto acquire = [&](uint32_t bytes) -> uint32_t {
        const uint32_t s = u & 7;
        mbar_wait(empty0 + 8 * s, ((u >> 3) & 1) ^ 1);
        mbar_expect_tx(full0 + 8 * s, bytes);
        u++;
        return s;
      };
      for (uint32_t n = 0;; n++) {
        int task;
        mbar_wait(tfull0 + 8 * (n & 3), (n >> 2) & 1);
        asm volatile("ld.shared.b32 %0, [%1];" : "=r"(task) : "r"(tbox + 4 * (n & 3)) : "memory");
        mbar_arrive(tempty0 + 8 * (n & 3));
        if (task < 0) break;
        const int type = task & 3, bsel = (task >> 2) & 1, pr = (task >> 3) & 3, h = (task >> 5) & 31, blk = (task >> 10) & 1;
        if (type != 2) {
          const CUtensorMap* mx = type ? &maps.x1[blk] : &maps.x[blk];
#pragma unroll 1
          for (int c = 0; c < 10; c++) {
            uint32_t s = acquire(type ? SLOT / 2 : SLOT);
            tma_2d(sbase + s * SLOT, mx, c * 64, pr * 192 + bsel * 96, full0 + 8 * s);
            s = acquire(SLOT);
            if (WQ_EF == 1 || (WQ_EF == 2 && pr == 3 && (type == 0 || bsel))) tma_4d_hint(sbase + s * SLOT, &maps.wq[blk], h * 3, c * 8, full0 + 8 * s, pol);
            else tma_4d(sbase + s * SLOT, &maps.wq[blk], h * 3, c * 8, full0 + 8 * s);
          }
        }
        int rg = (((pr * 2 + bsel) * NH + h) * SK) >> 3;
#pragma unroll 1
        for (int j = 0; j < 8; j++) {
          if (j == 8 - FETCH_AHEAD) mbar_arrive(sreq);
          if (KV_INFLIGHT < 8 && u >= KV_INFLIGHT) mbar_wait(full0 + 8 * ((u - KV_INFLIGHT) & 7), ((u - KV_INFLIGHT) >> 3) & 1);
          uint32_t s = acquire(SLOT);
          tma_4d_hint(sbase + s * SLOT, &maps.k[blk], 0, rg, full0 + 8 * s, pol);
          if (KV_INFLIGHT < 8 && u >= KV_INFLIGHT) mbar_wait(full0 + 8 * ((u - KV_INFLIGHT) & 7), ((u - KV_INFLIGHT) >> 3) & 1);
          s = acquire(SLOT);
          tma_4d_hint(sbase + s * SLOT, &maps.v[blk], 0, rg, full0 + 8 * s, pol);
          rg += 8;
        }
      }
    } else if (warp == 1 && lane == 0) {
      int task = ticket_task(blockIdx.x);
      for (uint32_t n = 0;; n++) {
        mbar_wait(tempty0 + 8 * (n & 3), ((n >> 2) & 1) ^ 1);
        asm volatile("st.shared.b32 [%0], %1;" :: "r"(tbox + 4 * (n & 3)), "r"(task) : "memory");
        mbar_arrive(tfull0 + 8 * (n & 3));
        if (task < 0) break;
        if ((task & 3) == 0) {
          task |= 2 | 4;
        } else {
          mbar_wait(sreq, n & 1);
          if ((int)blockIdx.x < N_OD) { task = -1; continue; }
          const unsigned int tk = atomicAdd(&g_ticket, 1u) + gridDim.x;
          task = tk < (unsigned)N_TICKETS ? ticket_task((int)tk) : -1;
          continue;
        }
        mbar_wait(sreq, n & 1);
      }
      __threadfence();
      if (atomicAdd(&g_done, 1u) == gridDim.x - 1) { g_ticket = 0; g_done = 0; }
    } else if (warp == 2 && lane == 0) {
      for (uint32_t n = 0;; n++) {
        int task;
        mbar_wait(tfull0 + 8 * (n & 3), (n >> 2) & 1);
        asm volatile("ld.shared.b32 %0, [%1];" : "=r"(task) : "r"(tbox + 4 * (n & 3)) : "memory");
        if (task < 0) break;
        mbar_wait(sig0 + 8 * (n & 3), (n >> 2) & 1);
        mbar_arrive(tempty0 + 8 * (n & 3));
        __threadfence();
        const int b = ((task >> 3) & 3) * 2 + ((task >> 2) & 1), h = (task >> 5) & 31, blk = (task >> 10) & 1;
        asm volatile("st.release.gpu.global.u32 [%0], %1;" :: "l"(&g_flag[(blk * NB + b) * NH + h]), "r"(6u) : "memory");
      }
    }
  } else {
    asm volatile("setmaxnreg.inc.sync.aligned.u32 240;");
    const int wg = (warp >> 2) - 1, w = warp & 3, tid = threadIdx.x & 127;
    Cons r; r.base = sbase; r.full0 = full0; r.it = 0; r.lane = lane;
    uint32_t qf[48];
    STAMP(0, 0);
    for (uint32_t n = 0;; n++) {
      int task;
      mbar_wait(tfull0 + 8 * (n & 3), (n >> 2) & 1);
      asm volatile("ld.shared.b32 %0, [%1];" : "=r"(task) : "r"(tbox + 4 * (n & 3)) : "memory");
      task = __shfl_sync(0xffffffffu, task, 0);
      if (lane == 0) mbar_arrive(tempty0 + 8 * (n & 3));
      if (task < 0) break;
      const int type = task & 3, bsel = (task >> 2) & 1, pr = (task >> 3) & 3, h = (task >> 5) & 31, blk = (task >> 10) & 1;
      const int b = pr * 2 + bsel;
      bool valid;
      int row8;
      if (type != 2) {
        qproj(r, qf, park, type == 0, wg, tid);
        if (wg == 1 && type == 0) asm volatile("bar.arrive 1, 256;" ::: "memory");
        valid = (wg == 0 || w < 2);
        row8 = wg * 8 + w * 2;
      } else {
        if (wg == 0) {
          asm volatile("bar.sync 1, 256;" ::: "memory");
#pragma unroll
          for (int ks = 0; ks < 12; ks++)
            asm volatile("ld.shared.v4.b32 {%0, %1, %2, %3}, [%4];" : "=r"(qf[4 * ks]), "=r"(qf[4 * ks + 1]), "=r"(qf[4 * ks + 2]), "=r"(qf[4 * ks + 3]) : "r"(park + (ks * 128 + tid) * 16) : "memory");
        }
        valid = (wg == 0 || w >= 2);
        row8 = wg == 0 ? 4 + w * 2 : (w - 2) * 2;
      }
      uint32_t* st = reinterpret_cast<uint32_t*>(g_stash) + (size_t)((blk * NH + h) * NB + b) * 9216 + row8 * 256;
      attention(r, qf, valid, st, sig0 + 8 * (n & 3), wg);
      STAMP(n + 1, task);
    }
  }
}

constexpr int NS2 = 9;
constexpr int SMEM2_BYTES = NS2 * SLOT + 1024 + 256;
constexpr int AX = N_OD - 20;
#define AE 20
#define B5 0
#define CHB4 0, 8, 16, 24, 32
#define CHB5 0, 7, 13, 19, 25, 32
constexpr int N_CTA2 = N_OD + (20 - AX) + 80 + B5;
static_assert(AX >= 0 && AX <= 20 && N_CTA2 <= 140, "bad O-projection table");

__global__ void __launch_bounds__(384, 1) oproj_kernel(const __grid_constant__ Maps maps, __nv_bfloat16* out) {
  extern __shared__ uint8_t smem_raw[];
  const uint32_t sbase = (smem_u32(smem_raw) + 1023u) & ~1023u;
  const uint32_t full0 = sbase + NS2 * SLOT, empty0 = full0 + 8 * NS2;
  const int warp = __shfl_sync(0xffffffffu, threadIdx.x >> 5, 0), lane = threadIdx.x & 31;
  const uint32_t ent = maps.otab[blockIdx.x];
  const int blk = ent & 1, tl = (ent >> 1) & 31, h0 = (ent >> 6) & 63, nh = (ent >> 12) & 63;
  const unsigned int nch = (ent >> 18) & 15;
  const bool fin = (ent >> 22) & 1;
  const int pr = tl & 3, nt = tl >> 2;
  if (threadIdx.x == 0) {
    for (int i = 0; i < NS2; i++) { mbar_init(full0 + 8 * i, 1); mbar_init(empty0 + 8 * i, 8); }
    asm volatile("prefetch.tensormap [%0];" :: "l"(&maps.wo[blk]) : "memory");
    asm volatile("fence.mbarrier_init.release.cluster;" ::: "memory");
  }
  uint32_t par;
  asm volatile("ld.relaxed.gpu.global.u32 %0, [%1];" : "=r"(par) : "l"(&g_epoch) : "memory");
  __syncthreads();

  if (warp < 4) {
    if (warp == 0) {
      uint32_t s = 0, ph = 1;
      const uint8_t* src = reinterpret_cast<const uint8_t*>(g_stash) + (size_t)((blk * NH + h0) * NB + pr * 2) * 36864;
      const unsigned int* fl = &g_flag[(blk * NB + pr * 2 + (lane >> 4)) * NH + h0 + (lane & 15)];
      unsigned int ready = 0;
#pragma unroll 1
      for (int hh = 0; hh < nh; hh++) {
        const int krow = (h0 + hh) * DH;
#pragma unroll 1
        for (int q = 0; q < 5; q++) {
          if (q == 1 && hh == 16) ready = 0;
          if (q == 1 && !((ready >> (hh & 15)) & 1)) {
            const bool watch = (hh & 16) + (lane & 15) < nh;
            for (int spin = 0; spin < (1 << 22); spin++) {
              const unsigned int m = __ballot_sync(0xffffffffu, !watch || ld_acquire(fl + (hh & 16)) == 6u);
              ready = m & (m >> 16);
              if ((ready >> (hh & 15)) & 1) break;
              __nanosleep(32);
            }
            asm volatile("fence.proxy.async;" ::: "memory");
          }
          if (lane == 0) {
            mbar_wait(empty0 + 8 * s, ph);
            mbar_expect_tx(full0 + 8 * s, SLOT);
            const uint32_t dst = sbase + s * SLOT, bar = full0 + 8 * s;
            if (q == 0 || q == 3) {
              tma_3d(dst, &maps.wo[blk], 0, krow + (q ? 96 : 0), nt * 2, bar);
            } else {
              const int kc = q == 4 ? 2 : q - 1;
              bulk_load(dst, src + kc * 12288, 12288, bar);
              bulk_load(dst + 12288, src + 36864 + kc * 12288, 12288, bar);
            }
          }
          __syncwarp();
          if (++s == NS2) { s = 0; ph ^= 1; }
        }
        src += NB * 36864;
      }
      if (fin && lane == 0) {
        const int tile = (blk * 4 + pr) * 5 + nt;
        for (int spin = 0; spin < (1 << 22) && ld_acquire(&g_tile_cnt[tile]) != (nch - 1) * 8; spin++) __nanosleep(32);
        g_tile_cnt[tile] = 0;
        asm volatile("fence.proxy.async;" ::: "memory");
        const uint8_t* ps = reinterpret_cast<const uint8_t*>(g_part[par]) + (size_t)tile * 4 * SLOT;
#pragma unroll 1
        for (int q = 0; q < 4; q++) {
          mbar_wait(empty0 + 8 * s, ph);
          mbar_expect_tx(full0 + 8 * s, SLOT);
          bulk_load(sbase + s * SLOT, ps + q * SLOT, SLOT, full0 + 8 * s);
          if (++s == NS2) { s = 0; ph ^= 1; }
        }
      }
      __syncwarp();
      asm volatile("griddepcontrol.wait;" ::: "memory");
      unsigned int d = 0;
      if (lane == 0) d = atomicAdd(&g_done2, 1u);
      if (__shfl_sync(0xffffffffu, d, 0) == gridDim.x - 1) {
        for (int i = lane; i < 2 * NB * NH; i += 32) g_flag[i] = 0;
        if (lane == 0) { g_done2 = 0; g_epoch = par ^ 1; }
      }
    }
  } else {
    const int wg = (warp >> 2) - 1, w = warp & 3, tid = threadIdx.x & 127;
    uint32_t s = 0, ph = 0;
    auto next = [&](uint32_t& slot) -> uint32_t {
      slot = s;
      mbar_wait(full0 + 8 * s, ph);
      if (++s == NS2) { s = 0; ph ^= 1; }
      return sbase + slot * SLOT;
    };
    auto release = [&](uint32_t slot) { if (lane == 0) mbar_arrive(empty0 + 8 * slot); };
    const int tile = (blk * 4 + pr) * 5 + nt;
    float acc[96];
    uint32_t pw1 = 0, po2 = 0;
    for (int hh = 0; hh < nh; hh++) {
      uint32_t sw0, so0, so1, sw1, so2;
      const uint64_t dw0 = desc_mnmajor_sw128<1024>(next(sw0) + wg * 12288);
      const uint64_t do0 = desc_kmajor_nosw(next(so0));
      wg_fence();
#pragma unroll
      for (int ks = 0; ks < 4; ks++) wgmma_st_n192_t0(acc, dw0 + ks * 128, do0 + ks * 16, (hh > 0 || ks > 0) ? 1 : 0);
      wg_commit();
      if (hh > 0) { wg_wait<1>(); release(pw1); release(po2); }
      else asm volatile("and.b32 %0, %0, 1;" : "+r"(par));
      const uint64_t do1 = desc_kmajor_nosw(next(so1));
      const uint64_t dw1 = desc_mnmajor_sw128<1024>(next(sw1) + wg * 12288);
      wg_fence();
      wgmma_st_n192_t0(acc, dw0 + 4 * 128, do1, 1);
      wgmma_st_n192_t0(acc, dw0 + 5 * 128, do1 + 16, 1);
      wgmma_st_n192_t0(acc, dw1, do1 + 32, 1);
      wgmma_st_n192_t0(acc, dw1 + 128, do1 + 48, 1);
      wg_commit();
      wg_wait<1>(); release(so0);
      const uint64_t do2 = desc_kmajor_nosw(next(so2));
      wg_fence();
#pragma unroll
      for (int ks = 0; ks < 4; ks++) wgmma_st_n192_t0(acc, dw1 + (2 + ks) * 128, do2 + ks * 16, 1);
      wg_commit();
      wg_wait<1>(); release(sw0); release(so1);
      pw1 = sw1; po2 = so2;
    }
    wg_wait<0>();
    touch(acc);
    float4* part = g_part[par] + (size_t)(tile * 2 + wg) * 24 * 128 + tid;
    if (!fin) {
      if (nch == 2) {
#pragma unroll
        for (int j = 0; j < 24; j++) __stcg(part + j * 128, make_float4(acc[4 * j], acc[4 * j + 1], acc[4 * j + 2], acc[4 * j + 3]));
      } else {
#pragma unroll
        for (int j = 0; j < 24; j++)
          asm volatile("red.global.add.v4.f32 [%0], {%1, %2, %3, %4};" :: "l"(part + j * 128), "f"(acc[4 * j]), "f"(acc[4 * j + 1]), "f"(acc[4 * j + 2]), "f"(acc[4 * j + 3]) : "memory");
      }
      __threadfence();
      __syncwarp();
      if (lane == 0) atomicAdd(&g_tile_cnt[tile], 1u);
      for (int i = (int)(ent >> 23) * 256 + (int)threadIdx.x - 128; i < 20 * 2 * 24 * 128; i += (N_CTA2 - 40) * 256)
        __stcg(g_part[par ^ 1] + 20 * 2 * 24 * 128 + i, make_float4(0.f, 0.f, 0.f, 0.f));
    } else {
      release(pw1); release(po2);
      asm volatile("bar.sync 3, 256;" ::: "memory");
      uint32_t sl, pa[4];
#pragma unroll
      for (int q = 0; q < 4; q++) {
        pa[q] = sbase + s * SLOT;
        if ((q >> 1) == wg) next(sl); else if (++s == NS2) { s = 0; ph ^= 1; }
      }
      const uint32_t s1 = s + 1 == NS2 ? 0 : s + 1;
      const uint32_t stg = sbase + (wg ? s1 : s) * SLOT;
      const int q = lane & 3;
      const bool odd = (lane >> 2) & 1;
      const int r8 = 2 * q + (odd ? 1 : 0);
      const uint32_t w0a = stg + r8 * 128 + (((2 * w) ^ r8) << 4) + (lane >> 3) * 4, w1a = stg + r8 * 128 + (((2 * w + 1) ^ r8) << 4) + (lane >> 3) * 4;
      const uint32_t p0 = (wg ? pa[2] : pa[0]) + tid * 16, p1 = (wg ? pa[3] : pa[1]) + tid * 16;
#pragma unroll
      for (int j = 0; j < 24; j++) {
        float4 e;
        asm volatile("ld.shared.v4.f32 {%0, %1, %2, %3}, [%4];" : "=f"(e.x), "=f"(e.y), "=f"(e.z), "=f"(e.w) : "r"((j < 12 ? p0 : p1) + (j % 12) * 2048) : "memory");
        const float x = acc[4 * j] + e.x, y = acc[4 * j + 1] + e.y, z = acc[4 * j + 2] + e.z, u = acc[4 * j + 3] + e.w;
        const float rx = __shfl_xor_sync(0xffffffffu, odd ? x : y, 4), rz = __shfl_xor_sync(0xffffffffu, odd ? z : u, 4);
        asm volatile("st.shared.b32 [%0], %1;" :: "r"(w0a + j * 1024), "r"(odd ? pack_bf16(rx, y) : pack_bf16(x, rx)) : "memory");
        asm volatile("st.shared.b32 [%0], %1;" :: "r"(w1a + j * 1024), "r"(odd ? pack_bf16(rz, u) : pack_bf16(z, rz)) : "memory");
      }
      asm volatile("bar.sync %0, 128;" :: "r"(1 + wg) : "memory");
      uint8_t* ob = reinterpret_cast<uint8_t*>(out + (size_t)(pr * 192) * (2 * DM) + blk * DM + nt * 128 + wg * 64);
#pragma unroll
      for (int i = 0; i < 12; i++) {
        const int row = i * 16 + (tid >> 3), ck = tid & 7;
        uint4 v;
        asm volatile("ld.shared.v4.b32 {%0, %1, %2, %3}, [%4];" : "=r"(v.x), "=r"(v.y), "=r"(v.z), "=r"(v.w) : "r"(stg + row * 128 + ((ck ^ (row & 7)) << 4)) : "memory");
        *reinterpret_cast<uint4*>(ob + (size_t)row * (4 * DM) + ck * 16) = v;
      }
    }
  }
}

typedef CUresult (*EncodeFn)(CUtensorMap*, CUtensorMapDataType, cuuint32_t, void*, const cuuint64_t*, const cuuint64_t*, const cuuint32_t*, const cuuint32_t*,
                             CUtensorMapInterleave, CUtensorMapSwizzle, CUtensorMapL2promotion, CUtensorMapFloatOOBfill);

void make_map(EncodeFn fn, CUtensorMap* m, const void* ptr, int rank, const uint64_t* dims, const uint64_t* strides, const uint32_t* box) {
  cuuint32_t es[4] = {1, 1, 1, 1};
  fn(m, CU_TENSOR_MAP_DATA_TYPE_BFLOAT16, rank, const_cast<void*>(ptr), dims, strides, box, es, CU_TENSOR_MAP_INTERLEAVE_NONE,
     CU_TENSOR_MAP_SWIZZLE_128B, L2PROMO, CU_TENSOR_MAP_FLOAT_OOB_FILL_NONE);
}

}

extern "C" void kernel_launch(void* const* d_in, const int* in_sizes, int n_in, void* d_out, int out_size) {
  static Maps maps;
  static const void* cached[10] = {nullptr};
  static bool init = false;
  static int grid = NCTA;
  bool same = init;
  for (int i = 0; i < 10; i++) same = same && (cached[i] == d_in[i]);
  if (!same) {
    void* fnp = nullptr;
    cudaDriverEntryPointQueryResult qr;
    cudaGetDriverEntryPoint("cuTensorMapEncodeTiled", &fnp, cudaEnableDefault, &qr);
    EncodeFn fn = (EncodeFn)fnp;
    for (int b = 0; b < 2; b++) {
      const void* x = d_in[5 * b + 0]; const void* k = d_in[5 * b + 1]; const void* v = d_in[5 * b + 2];
      const void* wq = d_in[5 * b + 3]; const void* wo = d_in[5 * b + 4];
      { uint64_t d[2] = {DM, NB * SQ}; uint64_t s[1] = {DM * 2}; uint32_t bx[2] = {64, 192}; make_map(fn, &maps.x[b], x, 2, d, s, bx);
        uint32_t b1[2] = {64, 96}; make_map(fn, &maps.x1[b], x, 2, d, s, b1); }
      { uint64_t d[4] = {64, 8, NH * DH / 64, DM / 8}; uint64_t s[3] = {NH * DH * 2, 128, 8 * NH * DH * 2}; uint32_t bx[4] = {64, 8, 3, 8}; make_map(fn, &maps.wq[b], wq, 4, d, s, bx); }
      { uint64_t d[4] = {64, 8, 3, (uint64_t)NB * NH * SK / 8}; uint64_t s[3] = {DH * 2, 128, 8 * DH * 2}; uint32_t bx[4] = {64, 8, 3, 8};
        make_map(fn, &maps.k[b], k, 4, d, s, bx); make_map(fn, &maps.v[b], v, 4, d, s, bx); }
      { uint64_t d[3] = {64, NH * DH, DM / 64}; uint64_t s[2] = {DM * 2, 128}; uint32_t bx[3] = {64, 96, 2}; make_map(fn, &maps.wo[b], wo, 3, d, s, bx); }
    }
    {
      const int b4[5] = {CHB4}, b5[6] = {CHB5};
      int n = 0, nz = 0;
      auto add = [&](int blk, int tl, int h0, int h1, int nch) { maps.otab[n++] = blk | (tl << 1) | (h0 << 6) | ((h1 - h0) << 12) | (nch << 18) | ((h1 == NH) << 22) | ((h1 == NH ? 0u : (unsigned)nz++) << 23); };
      for (int tl = 0; tl < 20; tl++) add(0, tl, 0, tl < AX ? 16 : AE, 2);
      for (int tl = 0; tl < 20; tl++) add(0, tl, tl < AX ? 16 : AE, 32, 2);
      for (int c = 0; c < 5; c++)
        for (int tl = 19; tl >= 0; tl--) {
          if (tl < B5) add(1, tl, b5[c], b5[c + 1], 5);
          else if (c < 3) add(1, tl, b4[c], b4[c + 1], 4);
          else if (c == 4) add(1, tl, b4[3], b4[4], 4);
        }
    }
    cudaFuncSetAttribute(attn_kernel, cudaFuncAttributeMaxDynamicSharedMemorySize, SMEM_BYTES);
    cudaFuncSetAttribute(oproj_kernel, cudaFuncAttributeMaxDynamicSharedMemorySize, SMEM2_BYTES);
    int dev = 0, sms = NCTA;
    cudaGetDevice(&dev);
    cudaDeviceGetAttribute(&sms, cudaDevAttrMultiProcessorCount, dev);
    grid = sms < NCTA ? sms : NCTA;
    for (int i = 0; i < 10; i++) cached[i] = d_in[i];
    init = true;
  }
  attn_kernel<<<grid, 384, SMEM_BYTES, cudaStreamPerThread>>>(maps);
  cudaLaunchConfig_t cfg = {};
  cfg.gridDim = dim3(N_CTA2); cfg.blockDim = dim3(384); cfg.dynamicSmemBytes = SMEM2_BYTES; cfg.stream = cudaStreamPerThread;
  cudaLaunchAttribute at[1];
  at[0].id = cudaLaunchAttributeProgrammaticStreamSerialization; at[0].val.programmaticStreamSerializationAllowed = PDL;
  cfg.attrs = at; cfg.numAttrs = 1;
  cudaLaunchKernelEx(&cfg, oproj_kernel, maps, (__nv_bfloat16*)d_out);
}
```
